```python
import torch

def _softmax(x, axis=-1):
    return torch.softmax(x, dim=axis)
def _gelu(x):
    return torch.nn.functional.gelu(x, approximate="tanh")
def _silu(x):
    return torch.nn.functional.silu(x)
def _sigmoid(x):
    return torch.sigmoid(x)
def _layernorm(x, axis=-1, eps=1e-5):
    m = x.mean(dim=axis, keepdim=True)
    v = x.var(dim=axis, keepdim=True, unbiased=False)
    return (x - m) / torch.sqrt(v + eps)
def _scatter_add(tgt, idx, src, axis=0):
    return tgt.clone().index_add_(axis, idx, src)
def _segment_sum(src, seg, n):
    out = torch.zeros((n,) + src.shape[1:], dtype=src.dtype)
    return out.index_add_(0, seg, src)
def _pad(x, pw):
    flat = tuple(v for pair in reversed(pw) for v in pair)
    return torch.nn.functional.pad(x, flat)

kernel_name = 'parallel_sum__spectral_fnet__swiglu_ffn__prompt'

def setup_inputs():

    _w = (lambda a: (lambda t: t.to(torch.bfloat16) if t.is_floating_point() else t)(torch.as_tensor(a)))
    def _A_setup():
        B, S, D = 1, 2048, 640
        ns = torch.arange(S)[:, None] * torch.arange(S)[None, :]
        nd = torch.arange(D)[:, None] * torch.arange(D)[None, :]
        Ws_re = torch.cos(-2.0 * torch.pi * ns / S).to(float)
        Ws_im = torch.sin(-2.0 * torch.pi * ns / S).to(float)
        Wd_re = torch.cos(-2.0 * torch.pi * nd / D).to(float)
        Wd_im = torch.sin(-2.0 * torch.pi * nd / D).to(float)
        return {
            "x": _w((lambda *s: torch.randn(*s, dtype=torch.bfloat16) * 0.05)(B, S, D)),
            "dft_seq_re": _w(Ws_re),
            "dft_seq_im": _w(Ws_im),
            "dft_hid_re": _w(Wd_re),
            "dft_hid_im": _w(Wd_im),
        }
    _A_in = _A_setup()

    def _B_setup():
        B, S, D, F = 1, 2048, 640, 1728
        return {
            "x": _w((lambda *s: torch.randn(*s, dtype=torch.bfloat16) * 0.05)(B, S, D)),
            "w_gate": _w((lambda *s: torch.randn(*s, dtype=torch.bfloat16) * 0.2)(D, F)),
            "w_up": _w((lambda *s: torch.randn(*s, dtype=torch.bfloat16) * 0.2)(D, F)),
            "w_down": _w((lambda *s: torch.randn(*s, dtype=torch.bfloat16) * 0.2)(F, D)),
        }
    _B_in = _B_setup()

    return {
        "A_x": _A_in["x"],
        "A_dft_seq_re": _A_in["dft_seq_re"],
        "A_dft_seq_im": _A_in["dft_seq_im"],
        "A_dft_hid_re": _A_in["dft_hid_re"],
        "A_dft_hid_im": _A_in["dft_hid_im"],
        "B_x": _B_in["x"],
        "B_w_gate": _B_in["w_gate"],
        "B_w_up": _B_in["w_up"],
        "B_w_down": _B_in["w_down"],
    }

def reference(A_x, A_dft_seq_re, A_dft_seq_im, A_dft_hid_re, A_dft_hid_im, B_x, B_w_gate, B_w_up, B_w_down):
    def _A_ref(x, dft_seq_re, dft_seq_im, dft_hid_re, dft_hid_im):
        a = torch.einsum("bsd,ed->bse", x, dft_hid_re)
        b = torch.einsum("bsd,ed->bse", x, dft_hid_im)
        y = torch.einsum("ts,bse->bte", dft_seq_re, a) - torch.einsum("ts,bse->bte", dft_seq_im, b)
        return y

    def _B_ref(x, w_gate, w_up, w_down):
        g = _silu(x @ w_gate)
        u = x @ w_up
        return (g * u) @ w_down

    x = A_x
    xn = _layernorm(x, axis=-1)
    return x + _A_ref(xn, A_dft_seq_re, A_dft_seq_im, A_dft_hid_re, A_dft_hid_im) + _B_ref(xn, B_w_gate, B_w_up, B_w_down)
```

```cpp
#include <cuda_runtime.h>
#include <cuda_bf16.h>
#include <cuda.h>
#include <stdint.h>

template<int TA, int TB, int SA> __device__ __forceinline__ void wgmma_ss_n80(float (&d)[40], uint64_t da, uint64_t db, int sd) {
  asm volatile("{\n.reg .pred p;\nsetp.ne.b32 p, %42, 0;\n"
    "wgmma.mma_async.sync.aligned.m64n80k16.f32.bf16.bf16 {%0, %1, %2, %3, %4, %5, %6, %7, %8, %9, %10, %11, %12, %13, %14, %15, %16, %17, %18, %19, %20, %21, %22, %23, %24, %25, %26, %27, %28, %29, %30, %31, %32, %33, %34, %35, %36, %37, %38, %39}, %40, %41, p, %45, 1, %43, %44;\n}\n"
    : "+f"(d[0]), "+f"(d[1]), "+f"(d[2]), "+f"(d[3]), "+f"(d[4]), "+f"(d[5]), "+f"(d[6]), "+f"(d[7]), "+f"(d[8]), "+f"(d[9]), "+f"(d[10]), "+f"(d[11]), "+f"(d[12]), "+f"(d[13]), "+f"(d[14]), "+f"(d[15]), "+f"(d[16]), "+f"(d[17]), "+f"(d[18]), "+f"(d[19]), "+f"(d[20]), "+f"(d[21]), "+f"(d[22]), "+f"(d[23]), "+f"(d[24]), "+f"(d[25]), "+f"(d[26]), "+f"(d[27]), "+f"(d[28]), "+f"(d[29]), "+f"(d[30]), "+f"(d[31]), "+f"(d[32]), "+f"(d[33]), "+f"(d[34]), "+f"(d[35]), "+f"(d[36]), "+f"(d[37]), "+f"(d[38]), "+f"(d[39])
    : "l"(da), "l"(db), "r"(sd), "n"(TA), "n"(TB), "n"(SA));
}
template<int TA, int TB, int SA> __device__ __forceinline__ void wgmma_ss_n128(float (&d)[64], uint64_t da, uint64_t db, int sd) {
  asm volatile("{\n.reg .pred p;\nsetp.ne.b32 p, %66, 0;\n"
    "wgmma.mma_async.sync.aligned.m64n128k16.f32.bf16.bf16 {%0, %1, %2, %3, %4, %5, %6, %7, %8, %9, %10, %11, %12, %13, %14, %15, %16, %17, %18, %19, %20, %21, %22, %23, %24, %25, %26, %27, %28, %29, %30, %31, %32, %33, %34, %35, %36, %37, %38, %39, %40, %41, %42, %43, %44, %45, %46, %47, %48, %49, %50, %51, %52, %53, %54, %55, %56, %57, %58, %59, %60, %61, %62, %63}, %64, %65, p, %69, 1, %67, %68;\n}\n"
    : "+f"(d[0]), "+f"(d[1]), "+f"(d[2]), "+f"(d[3]), "+f"(d[4]), "+f"(d[5]), "+f"(d[6]), "+f"(d[7]), "+f"(d[8]), "+f"(d[9]), "+f"(d[10]), "+f"(d[11]), "+f"(d[12]), "+f"(d[13]), "+f"(d[14]), "+f"(d[15]), "+f"(d[16]), "+f"(d[17]), "+f"(d[18]), "+f"(d[19]), "+f"(d[20]), "+f"(d[21]), "+f"(d[22]), "+f"(d[23]), "+f"(d[24]), "+f"(d[25]), "+f"(d[26]), "+f"(d[27]), "+f"(d[28]), "+f"(d[29]), "+f"(d[30]), "+f"(d[31]), "+f"(d[32]), "+f"(d[33]), "+f"(d[34]), "+f"(d[35]), "+f"(d[36]), "+f"(d[37]), "+f"(d[38]), "+f"(d[39]), "+f"(d[40]), "+f"(d[41]), "+f"(d[42]), "+f"(d[43]), "+f"(d[44]), "+f"(d[45]), "+f"(d[46]), "+f"(d[47]), "+f"(d[48]), "+f"(d[49]), "+f"(d[50]), "+f"(d[51]), "+f"(d[52]), "+f"(d[53]), "+f"(d[54]), "+f"(d[55]), "+f"(d[56]), "+f"(d[57]), "+f"(d[58]), "+f"(d[59]), "+f"(d[60]), "+f"(d[61]), "+f"(d[62]), "+f"(d[63])
    : "l"(da), "l"(db), "r"(sd), "n"(TA), "n"(TB), "n"(SA));
}
template<int TA, int TB, int SA> __device__ __forceinline__ void wgmma_ss_n160(float (&d)[80], uint64_t da, uint64_t db, int sd) {
  asm volatile("{\n.reg .pred p;\nsetp.ne.b32 p, %82, 0;\n"
    "wgmma.mma_async.sync.aligned.m64n160k16.f32.bf16.bf16 {%0, %1, %2, %3, %4, %5, %6, %7, %8, %9, %10, %11, %12, %13, %14, %15, %16, %17, %18, %19, %20, %21, %22, %23, %24, %25, %26, %27, %28, %29, %30, %31, %32, %33, %34, %35, %36, %37, %38, %39, %40, %41, %42, %43, %44, %45, %46, %47, %48, %49, %50, %51, %52, %53, %54, %55, %56, %57, %58, %59, %60, %61, %62, %63, %64, %65, %66, %67, %68, %69, %70, %71, %72, %73, %74, %75, %76, %77, %78, %79}, %80, %81, p, %85, 1, %83, %84;\n}\n"
    : "+f"(d[0]), "+f"(d[1]), "+f"(d[2]), "+f"(d[3]), "+f"(d[4]), "+f"(d[5]), "+f"(d[6]), "+f"(d[7]), "+f"(d[8]), "+f"(d[9]), "+f"(d[10]), "+f"(d[11]), "+f"(d[12]), "+f"(d[13]), "+f"(d[14]), "+f"(d[15]), "+f"(d[16]), "+f"(d[17]), "+f"(d[18]), "+f"(d[19]), "+f"(d[20]), "+f"(d[21]), "+f"(d[22]), "+f"(d[23]), "+f"(d[24]), "+f"(d[25]), "+f"(d[26]), "+f"(d[27]), "+f"(d[28]), "+f"(d[29]), "+f"(d[30]), "+f"(d[31]), "+f"(d[32]), "+f"(d[33]), "+f"(d[34]), "+f"(d[35]), "+f"(d[36]), "+f"(d[37]), "+f"(d[38]), "+f"(d[39]), "+f"(d[40]), "+f"(d[41]), "+f"(d[42]), "+f"(d[43]), "+f"(d[44]), "+f"(d[45]), "+f"(d[46]), "+f"(d[47]), "+f"(d[48]), "+f"(d[49]), "+f"(d[50]), "+f"(d[51]), "+f"(d[52]), "+f"(d[53]), "+f"(d[54]), "+f"(d[55]), "+f"(d[56]), "+f"(d[57]), "+f"(d[58]), "+f"(d[59]), "+f"(d[60]), "+f"(d[61]), "+f"(d[62]), "+f"(d[63]), "+f"(d[64]), "+f"(d[65]), "+f"(d[66]), "+f"(d[67]), "+f"(d[68]), "+f"(d[69]), "+f"(d[70]), "+f"(d[71]), "+f"(d[72]), "+f"(d[73]), "+f"(d[74]), "+f"(d[75]), "+f"(d[76]), "+f"(d[77]), "+f"(d[78]), "+f"(d[79])
    : "l"(da), "l"(db), "r"(sd), "n"(TA), "n"(TB), "n"(SA));
}

namespace {

constexpr int S_ = 2048, D_ = 640, F_ = 1728;
constexpr int A_CHUNK   = 16384;
constexpr int RING1_OFF = 10 * A_CHUNK;
constexpr int R1        = 4;
constexpr int SLOT2     = 36864;
constexpr int R2        = 6;
constexpr int BAR_OFF   = RING1_OFF + R1 * 16384;
constexpr int TL_OFF    = BAR_OFF + 512;
constexpr int SMEM_BYTES = TL_OFF + 512;
constexpr int NUM_CTAS  = 132;
#define NC1 38
#define ND1 13
#define DPF_NS 500
#define WPF_NS 700
#define PF 0

__device__ __nv_bfloat16 g_xn[S_ * D_];
__device__ __nv_bfloat16 g_abT[2 * D_ * S_];
__device__ __nv_bfloat16 g_hT[F_ * S_];
constexpr int CNT_XN = 0, CNT_H = 16, CNT_HX = 32, CNT_AB = 48, CNT_DONE = 49, CNT_TOTAL = 50;
__device__ unsigned g_cnt[CNT_TOTAL * 32];
#define TL(idx) do {} while (0)

struct Params {
  const __nv_bfloat16* x; __nv_bfloat16* out;
  __nv_bfloat16* xn; unsigned* cnt; __nv_bfloat16* abT; __nv_bfloat16* hT;
  const __nv_bfloat16 *dr, *di, *wg, *wu, *wd;
};
struct Maps {
  CUtensorMap xn, dr, di, wg, wu, cr, ci, h, ab, wd;
};

__device__ __forceinline__ uint32_t smem_u32(const void* p) { return (uint32_t)__cvta_generic_to_shared(p); }
__device__ __forceinline__ void mbar_init(uint32_t bar, uint32_t count) { asm volatile("mbarrier.init.shared::cta.b64 [%0], %1;" :: "r"(bar), "r"(count)); }
__device__ __forceinline__ void mbar_expect_tx(uint32_t bar, uint32_t bytes) { asm volatile("mbarrier.arrive.expect_tx.shared::cta.b64 _, [%0], %1;" :: "r"(bar), "r"(bytes) : "memory"); }
__device__ __forceinline__ void mbar_arrive(uint32_t bar) { asm volatile("mbarrier.arrive.shared::cta.b64 _, [%0];" :: "r"(bar) : "memory"); }
__device__ __forceinline__ void mbar_arrive_cta(uint32_t bar, uint32_t cta) {
  asm volatile("{\n.reg .b32 ra;\nmapa.shared::cluster.u32 ra, %0, %1;\nmbarrier.arrive.shared::cluster.b64 _, [ra];\n}\n" :: "r"(bar), "r"(cta) : "memory");
}
__device__ __forceinline__ void mbar_wait(uint32_t bar, uint32_t parity) {
  asm volatile("{\n.reg .pred p;\n.reg .u32 n;\nmov.u32 n, 0;\n"
    "LAB_WAIT:\n"
    "mbarrier.try_wait.parity.shared::cta.b64 p, [%0], %1;\n"
    "@p bra LAB_DONE;\n"
    "add.u32 n, n, 1;\n"
    "setp.lt.u32 p, n, 4000000;\n"
    "@p bra LAB_WAIT;\n"
    "trap;\n"
    "LAB_DONE:\n}\n" :: "r"(bar), "r"(parity) : "memory");
}
__device__ __forceinline__ void tma_load(uint32_t dst, const CUtensorMap* map, int c0, int c1, uint32_t bar) {
  asm volatile("cp.async.bulk.tensor.2d.shared::cluster.global.mbarrier::complete_tx::bytes [%0], [%1, {%3, %4}], [%2];"
    :: "r"(dst), "l"(map), "r"(bar), "r"(c0), "r"(c1) : "memory");
}
__device__ __forceinline__ void tma_load_mc(uint32_t dst, const CUtensorMap* map, int c0, int c1, uint32_t bar) {
  asm volatile("cp.async.bulk.tensor.2d.shared::cluster.global.mbarrier::complete_tx::bytes.multicast::cluster [%0], [%1, {%3, %4}], [%2], %5;"
    :: "r"(dst), "l"(map), "r"(bar), "r"(c0), "r"(c1), "h"((uint16_t)3) : "memory");
}
__device__ __forceinline__ void tma_load_3d(uint32_t dst, const CUtensorMap* map, int c1, int c2, uint32_t bar) {
  asm volatile("cp.async.bulk.tensor.3d.shared::cluster.global.mbarrier::complete_tx::bytes [%0], [%1, {%5, %3, %4}], [%2];"
    :: "r"(dst), "l"(map), "r"(bar), "r"(c1), "r"(c2), "r"(0) : "memory");
}
__device__ __forceinline__ void tma_load_3d_mc(uint32_t dst, const CUtensorMap* map, int c1, int c2, uint32_t bar) {
  asm volatile("cp.async.bulk.tensor.3d.shared::cluster.global.mbarrier::complete_tx::bytes.multicast::cluster [%0], [%1, {%5, %3, %4}], [%2], %6;"
    :: "r"(dst), "l"(map), "r"(bar), "r"(c1), "r"(c2), "r"(0), "h"((uint16_t)3) : "memory");
}
__device__ __forceinline__ void tma_prefetch(const CUtensorMap* map, int c0, int c1) {
  asm volatile("cp.async.bulk.prefetch.tensor.2d.L2.global [%0, {%1, %2}];" :: "l"(map), "r"(c0), "r"(c1) : "memory");
}
__device__ __forceinline__ void prefetch_map(const CUtensorMap* map) { asm volatile("prefetch.tensormap [%0];" :: "l"(map) : "memory"); }
__device__ __forceinline__ void l2_prefetch(const void* p, uint32_t bytes) { asm volatile("cp.async.bulk.prefetch.L2.global [%0], %1;" :: "l"(p), "r"(bytes) : "memory"); }
__device__ __forceinline__ void wgmma_fence() { asm volatile("wgmma.fence.sync.aligned;" ::: "memory"); }
__device__ __forceinline__ void wgmma_commit() { asm volatile("wgmma.commit_group.sync.aligned;" ::: "memory"); }
template<int N> __device__ __forceinline__ void wgmma_wait() { asm volatile("wgmma.wait_group.sync.aligned %0;" :: "n"(N) : "memory"); }
template<int N> __device__ __forceinline__ void fence_acc(float (&d)[N]) {
  #pragma unroll
  for (int i = 0; i < N; i++) asm volatile("" : "+f"(d[i]) :: "memory");
}
__device__ __forceinline__ void named_sync(int id, int n) { asm volatile("bar.sync %0, %1;" :: "r"(id), "r"(n) : "memory"); }
__device__ __forceinline__ void named_arrive(int id, int n) { asm volatile("bar.arrive %0, %1;" :: "r"(id), "r"(n) : "memory"); }
template<int R> __device__ __forceinline__ void reg_alloc() { asm volatile("setmaxnreg.inc.sync.aligned.u32 %0;" :: "n"(R)); }
template<int R> __device__ __forceinline__ void reg_dealloc() { asm volatile("setmaxnreg.dec.sync.aligned.u32 %0;" :: "n"(R)); }
__device__ __forceinline__ void fence_proxy_async_global() { asm volatile("fence.proxy.async.global;" ::: "memory"); }
__device__ __forceinline__ void red_release(unsigned* p) { asm volatile("red.release.gpu.global.add.u32 [%0], 1;" :: "l"(p) : "memory"); }
template<int SLEEP_NS>
__device__ __forceinline__ void wait_counter(const unsigned* p, unsigned target) {
  asm volatile("{\n.reg .pred p;\n.reg .u32 n, v;\nmov.u32 n, 0;\n"
    "LAB_WAIT:\n"
    "ld.acquire.gpu.global.u32 v, [%0];\n"
    "setp.ge.u32 p, v, %1;\n"
    "@p bra LAB_DONE;\n"
    "nanosleep.u32 %2;\n"
    "add.u32 n, n, 1;\n"
    "setp.lt.u32 p, n, 2000000;\n"
    "@p bra LAB_WAIT;\n"
    "trap;\n"
    "LAB_DONE:\n}\n" :: "l"(p), "r"(target), "n"(SLEEP_NS) : "memory");
}
constexpr uint32_t HI_SW128 = (1024 >> 4) | (1u << 30);
constexpr uint32_t HI_SW64  = (512 >> 4) | (2u << 30);
constexpr uint32_t DBASE    = 0x400 >> 4;
constexpr uint32_t LBO_NONE = 1u << 16;
constexpr uint32_t LBO_2K   = (2048u >> 4) << 16;
__device__ __forceinline__ uint64_t mk_desc(uint32_t lo, uint32_t hi) { uint64_t d; asm("mov.b64 %0, {%1, %2};" : "=l"(d) : "r"(lo), "r"(hi)); return d; }

__device__ __forceinline__ uint32_t pack_bf16(float lo, float hi) {
  uint32_t r; asm("cvt.rn.bf16x2.f32 %0, %1, %2;" : "=r"(r) : "f"(hi), "f"(lo)); return r;
}
__device__ __forceinline__ float bf_lo(uint32_t v) { return __uint_as_float(v << 16); }
__device__ __forceinline__ float bf_hi(uint32_t v) { return __uint_as_float(v & 0xffff0000u); }
__device__ __forceinline__ float round_bf(float v) { return bf_lo(pack_bf16(v, 0.f)); }
__device__ __forceinline__ float silu_mul(float g, float u) {
  float e, r;
  asm("ex2.approx.ftz.f32 %0, %1;" : "=f"(e) : "f"(g * -1.4426950408889634f));
  asm("rcp.approx.ftz.f32 %0, %1;" : "=f"(r) : "f"(e + 1.0f));
  return (g * u) * r;
}
__device__ __forceinline__ int xn_row(int t) { return (t & ~30) | ((t & 6) << 2) | ((t & 24) >> 2); }
__device__ __forceinline__ int unit_of(int role, int t) {
  const int two_ab = (role & 5) == 0;
  if (t == 0) return role;
  if (t == 1 && two_ab) return 8 + (role >> 1);
  return 9 + 3 * role + (role > 4) + (role > 6) + t - two_ab;
}

struct Ctx {
  uint32_t sbase, full1, empty1, full2, empty2, flagb, pub, xfull;
  int wg, warp, lane, zero;
  bool elect;
};

template<int MODE, bool LAST>
__device__ __forceinline__ void stage1_mma(const Ctx& c, float (&acc)[2][64], int it0, bool first, bool has_next, bool free_all) {
  int prev = 0;
  #pragma unroll 1
  for (int kb = 0; kb < 10; kb++) {
    const int it = it0 + kb;
    const int slot = it & 3;
    const uint32_t bx = DBASE + kb * (A_CHUNK >> 4) + LBO_NONE;
    const uint32_t ar = DBASE + slot * 1024 + ((RING1_OFF >> 4) + LBO_NONE);
    if (MODE != 2 && first) mbar_wait(c.xfull + 8 * kb, 0);
    mbar_wait(c.full1 + 8 * slot, (it >> 2) & 1);
    if (kb == 9 && has_next) named_arrive(1 + (c.wg ^ 1), 256);
    wgmma_fence();
    #pragma unroll
    for (int k = 0; k < 4; k++) {
      #pragma unroll
      for (int i = 0; i < 2; i++) {
        if (MODE == 2) wgmma_ss_n128<1, 0, 1>(acc[i], mk_desc(ar + i * 512 + k * 128, HI_SW128), mk_desc(bx + k * 2, HI_SW128), (kb | k) != 0);
        else           wgmma_ss_n128<0, 0, (MODE == 1 ? -1 : 1)>(acc[i], mk_desc(ar + i * 512 + k * 2, HI_SW128), mk_desc(bx + k * 2, HI_SW128), (kb | k) != 0);
      }
    }
    wgmma_commit();
    wgmma_wait<1>();
    if (kb > 0 && c.elect) {
      mbar_arrive(c.empty1 + 8 * prev);
      if (LAST && kb >= 3 && (kb & 1)) {
        const uint32_t b = c.empty2 + 8 * ((kb - 3) >> 1);
        mbar_arrive_cta(b, 0); mbar_arrive_cta(b, 1);
      }
    }
    prev = slot;
  }
  #pragma unroll 1
  for (int z = c.zero; z < 1; z++) {
    wgmma_wait<0>();
    if (c.elect) {
      mbar_arrive(c.empty1 + 8 * prev);
      TL(33 + (it0 / 10) * 4);
      if (LAST || free_all) {
        #pragma unroll
        for (int j = LAST ? 4 : 0; j < R2; j++) { mbar_arrive_cta(c.empty2 + 8 * j, 0); mbar_arrive_cta(c.empty2 + 8 * j, 1); }
      }
    }
  }
  wgmma_wait<0>();
  fence_acc(acc[0]); fence_acc(acc[1]);
}
__device__ __forceinline__ void store_ab(const float (&acc)[2][64], uint4* dst) {
  #pragma unroll
  for (int i = 0; i < 2; i++)
    #pragma unroll
    for (int hf = 0; hf < 2; hf++)
      #pragma unroll
      for (int J = 0; J < 4; J++) {
        const int r = 16 * J + 2 * hf;
        dst[(i * 64 + hf * 8) * (S_ / 8) + J * 4] = make_uint4(pack_bf16(acc[i][r], acc[i][r + 1]), pack_bf16(acc[i][r + 4], acc[i][r + 5]),
                                                               pack_bf16(acc[i][r + 8], acc[i][r + 9]), pack_bf16(acc[i][r + 12], acc[i][r + 13]));
      }
}
__device__ __forceinline__ void store_h_slice(const float (&acc)[2][64], uint4* dst, int sl) {
  const int hf = sl >> 2, J = sl & 3;
  uint32_t w[4];
  #pragma unroll
  for (int b = 0; b < 4; b++) {
    const int r = 16 * J + 4 * b + 2 * hf;
    w[b] = pack_bf16(silu_mul(acc[0][r], acc[1][r]), silu_mul(acc[0][r + 1], acc[1][r + 1]));
  }
  dst[hf * 8 * (S_ / 8) + J * 4] = make_uint4(w[0], w[1], w[2], w[3]);
}
__device__ __forceinline__ void publish(const Ctx& c, int t) {
  if (c.elect) TL(34 + t * 4);
  __syncwarp();
  if (c.lane == 0) mbar_arrive(c.pub + 8 * t);
}
__device__ __forceinline__ void stage2_c(const Ctx& c, float (&acc)[80], int slot, int ph, bool accumulate) {
  const uint32_t sa = DBASE + slot * (SLOT2 >> 4) + c.wg * 512 + LBO_NONE, sb = DBASE + slot * (SLOT2 >> 4) + (1024 + LBO_NONE);
  mbar_wait(c.full2 + 8 * slot, ph);
  wgmma_fence();
  #pragma unroll
  for (int k = 0; k < 4; k++) wgmma_ss_n160<0, 0, 1>(acc, mk_desc(sa + k * 2, HI_SW128), mk_desc(sb + k * 2, HI_SW128), accumulate || k != 0);
  wgmma_commit();
}
__device__ __forceinline__ void release2(const Ctx& c, int slot) {
  if (c.elect) { mbar_arrive_cta(c.empty2 + 8 * slot, 0); mbar_arrive_cta(c.empty2 + 8 * slot, 1); }
}

template<int KH>
__device__ __forceinline__ void stage2_finish(const Ctx& c, float (&acc)[80], const uint32_t (&xr)[2][10], __nv_bfloat16* outw) {
  #pragma unroll
  for (int j = 0; j < 10; j++) {
    acc[KH * 40 + 4 * j] += bf_lo(xr[0][j]); acc[KH * 40 + 4 * j + 1] += bf_hi(xr[0][j]);
    acc[KH * 40 + 4 * j + 2] += bf_lo(xr[1][j]); acc[KH * 40 + 4 * j + 3] += bf_hi(xr[1][j]);
  }
  const uint32_t stg = c.sbase + c.warp * SLOT2 + c.wg * 8192;
  const uint32_t sw = stg + (c.lane & 15) * 336 + (c.lane >> 4) * 16;
  #pragma unroll
  for (int jj = 0; jj < 10; jj++) {
    asm volatile("stmatrix.sync.aligned.m8n8.x4.shared.b16 [%0], {%1, %2, %3, %4};" :: "r"(sw + jj * 32),
                 "r"(pack_bf16(acc[8 * jj], acc[8 * jj + 1])), "r"(pack_bf16(acc[8 * jj + 2], acc[8 * jj + 3])),
                 "r"(pack_bf16(acc[8 * jj + 4], acc[8 * jj + 5])), "r"(pack_bf16(acc[8 * jj + 6], acc[8 * jj + 7])) : "memory");
  }
  __syncwarp();
  uint4 v[10];
  #pragma unroll
  for (int i = 0; i < 10; i++) {
    const int idx = i * 32 + c.lane, row = idx / 20, ch = idx - row * 20;
    asm volatile("ld.shared.v4.u32 {%0, %1, %2, %3}, [%4];" : "=r"(v[i].x), "=r"(v[i].y), "=r"(v[i].z), "=r"(v[i].w) : "r"(stg + row * 336 + ch * 16) : "memory");
  }
  #pragma unroll
  for (int i = 0; i < 10; i++) {
    const int idx = i * 32 + c.lane, row = idx / 20, ch = idx - row * 20;
    asm volatile("red.global.add.noftz.v4.bf16x2 [%0], {%1, %2, %3, %4};" :: "l"(outw + row * D_ + ch * 8), "r"(v[i].x), "r"(v[i].y), "r"(v[i].z), "r"(v[i].w) : "memory");
  }
}

__global__ void __launch_bounds__(384, 1)
fused_kernel(const __grid_constant__ Params p, const __grid_constant__ Maps maps) {
  extern __shared__ __align__(1024) uint8_t smem_raw[];
  const int cl = blockIdx.x >> 1, rank = blockIdx.x & 1;
  const bool extra = cl >= 64;
  const int tok = (blockIdx.x & 127) * 16 + ((threadIdx.x >> 4) & 15), l16 = threadIdx.x & 15;
  uint4 v[5];
  uint32_t x0 = 0;
  if (threadIdx.x < 256) {
    const uint4* xs = reinterpret_cast<const uint4*>(p.x + (size_t)tok * D_);
    #pragma unroll
    for (int i = 0; i < 5; i++) v[i] = __ldg(xs + l16 + 16 * i);
    x0 = __ldg(reinterpret_cast<const uint32_t*>(xs));
  }
  const int kh = cl & 1, nt = (cl >> 1) & 3;
  const int mb2 = (cl >> 3) * 2 + rank;
  const int role = kh + 2 * ((nt & 1) * 2 + rank);
  const int mb1 = extra ? (cl - 64) * 8 + rank : (cl >> 2);

  Ctx c;
  c.sbase = __shfl_sync(0xffffffffu, smem_u32(smem_raw), 0);
  c.zero = __shfl_sync(0xffffffffu, threadIdx.x >> 10, 0);
  c.full1 = c.sbase + BAR_OFF; c.empty1 = c.full1 + 8 * R1; c.full2 = c.empty1 + 8 * R1; c.empty2 = c.full2 + 8 * R2;
  c.flagb = c.empty2 + 8 * R2; c.pub = c.flagb + 8 * 3; c.xfull = c.pub + 8 * 5;
  c.wg = __shfl_sync(0xffffffffu, threadIdx.x >> 7, 0);
  c.warp = __shfl_sync(0xffffffffu, (threadIdx.x >> 5) & 3, 0);
  c.lane = threadIdx.x & 31;
  c.elect = (threadIdx.x & 127) == 0;

  const int nT = extra ? 4 : 5 - kh;
  const int nC = kh ? NC1 : 64 - NC1, c0 = kh ? 0 : NC1, nD = kh ? ND1 : 27 - ND1, d0 = kh ? 0 : ND1;
  const int n2 = nC + nD;

  if (c.wg == 2) {
    reg_dealloc<40>();
    int wlo = c.warp & 1, whi = c.warp >> 1;
    asm volatile("" : "+r"(wlo)); asm volatile("" : "+r"(whi));
    const bool w0 = !whi && !wlo, w1 = !whi && wlo, w2 = whi && !wlo;
    if (c.lane == 0) {
      if (w0) {
        #pragma unroll
        for (int i = 0; i < 2 * R1; i++) mbar_init(c.full1 + 8 * i, 1);
      } else if (w1) {
        prefetch_map(&maps.xn);
        #pragma unroll
        for (int i = 0; i < 10; i++) mbar_init(c.xfull + 8 * i, 1);
      } else if (w2) {
        #pragma unroll
        for (int i = 0; i < R2; i++) { mbar_init(c.full2 + 8 * i, 1); mbar_init(c.empty2 + 8 * i, 4); }
      } else {
        #pragma unroll
        for (int i = 0; i < 3; i++) mbar_init(c.flagb + 8 * i, 1);
        #pragma unroll
        for (int i = 0; i < 5; i++) mbar_init(c.pub + 8 * i, 4);
        if ((c.sbase & 0x3FFFFu) != 0x400u) asm volatile("trap;");
      }
      asm volatile("fence.mbarrier_init.release.cluster;" ::: "memory");
      if (w0) TL(11);
    }
    __syncwarp();
    asm volatile("barrier.cluster.arrive.relaxed.aligned;" ::: "memory");
    asm volatile("barrier.cluster.wait.acquire.aligned;" ::: "memory");
    if (w0) {
      if (c.lane == 0) {
        int it = 0;
        for (int t = 0; t < nT; t++) {
          const int unit = extra ? 36 : unit_of(role, t);
          for (int kb = 0; kb < 10; kb++, it++) {
            const int slot = it & 3;
            const uint32_t full = c.full1 + 8 * slot;
            const uint32_t dst = c.sbase + RING1_OFF + slot * 16384;
            mbar_wait(c.empty1 + 8 * slot, ((it >> 2) & 1) ^ 1);
            mbar_expect_tx(full, extra ? 32768 : 16384);
            if (unit < 10) {
              tma_load(dst, unit < 5 ? &maps.dr : &maps.di, kb * 64, (unit < 5 ? unit : unit - 5) * 128, full);
            } else {
              tma_load(dst, &maps.wg, (unit - 10) * 64, kb * 64, full);
              tma_load(dst + 8192, &maps.wu, (unit - 10) * 64, kb * 64, full);
            }
            if (it == 3) { TL(12); prefetch_map(&maps.wg); prefetch_map(&maps.wu); prefetch_map(&maps.di); }
            if (extra) {
              if (kb == 0) { wait_counter<100>(&p.cnt[(CNT_XN + mb1 + 2 * t) * 32], 8); fence_proxy_async_global(); }
              tma_load(c.sbase + kb * A_CHUNK, &maps.xn, kb * 64, (mb1 + 2 * t) * 128, full);
            }
          }
        }
      }
    } else if (w1) {
      if (c.lane == 0 && !extra) {
        #pragma unroll
        for (int i = 0; i < 10; i++) mbar_expect_tx(c.xfull + 8 * i, A_CHUNK);
        wait_counter<0>(&p.cnt[(CNT_XN + mb1) * 32], 8);
        fence_proxy_async_global();
        TL(1);
        #pragma unroll
        for (int i = 0; i < 5; i++) tma_load_mc(c.sbase + (2 * i + rank) * A_CHUNK, &maps.xn, (2 * i + rank) * 64, mb1 * 128, c.xfull + 8 * (2 * i + rank));
        TL(14);
        prefetch_map(&maps.cr); prefetch_map(&maps.ci); prefetch_map(&maps.ab); prefetch_map(&maps.h); prefetch_map(&maps.wd);
        int slot = 0, ph = 0;
        for (int i = 0; i < n2; i++) {
          if (PF > 0 && ((i + PF) & 3) == nt && i + PF < nC) { const int kc = c0 + i + PF; tma_prefetch(kc >= 32 ? &maps.ci : &maps.cr, (kc & 31) * 64, mb2 * 128); }
          const uint32_t full = c.full2 + 8 * slot;
          const uint32_t dst = c.sbase + slot * SLOT2;
          mbar_wait(c.empty2 + 8 * slot, ph);
          if (i == 0) { TL(2); mbar_wait(c.flagb, 0); fence_proxy_async_global(); TL(3); }
          mbar_expect_tx(full, SLOT2);
          if (i < nC) {
            const int kc = c0 + i;
            const int im = kc >= 32;
            const int kk = (kc & 31) * 64;
            tma_load(dst, im ? &maps.ci : &maps.cr, kk, mb2 * 128, full);
            tma_load_mc(dst + 16384 + rank * 10240, &maps.ab, kk, im * 640 + nt * 160 + rank * 80, full);
          } else {
            const int kd = d0 + i - nC;
            tma_load_3d_mc(dst + 16384 + rank * 10240, &maps.wd, kd * 64 + rank * 32, nt * 5, full);
            if (i == nC) { TL(4); mbar_wait(c.flagb + 8, 0); fence_proxy_async_global(); TL(5); }
            if (kd == 26) { mbar_wait(c.flagb + 16, 0); fence_proxy_async_global(); }
            tma_load_3d(dst, &maps.h, kd * 64, mb2 * 2, full);
          }
          if (++slot == R2) { slot = 0; ph ^= 1; }
        }
      }
    } else if (w2) {
      const uint32_t totd = D_ * D_ * 2, perd = ((totd + NUM_CTAS - 1) / NUM_CTAS + 127) & ~127u, begd = blockIdx.x * perd;
      const uint32_t total = D_ * F_ * 2, per = ((total + NUM_CTAS - 1) / NUM_CTAS + 127) & ~127u, beg = blockIdx.x * per;
      __nanosleep(DPF_NS);
      if (c.lane < 2 && begd < totd) l2_prefetch((const char*)(c.lane ? p.dr : p.di) + begd, min(perd, totd - begd));
      __nanosleep(WPF_NS);
      if (c.lane < 2 && beg < total) l2_prefetch((const char*)(c.lane ? p.wg : p.wu) + beg, min(per, total - beg));
      __nanosleep(3500);
      if (!extra) {
        __nv_bfloat16* zb = p.out + (size_t)mb2 * 128 * D_ + nt * 160 + kh * 80;
        #pragma unroll 4
        for (int i = c.lane; i < 1280; i += 32) { const int r = i / 10; *reinterpret_cast<uint4*>(zb + r * D_ + (i - r * 10) * 8) = make_uint4(0u, 0u, 0u, 0u); }
      }
      __syncwarp();
      if (c.lane == 1) {
        __nanosleep(6000);
        if (beg < total) l2_prefetch((const char*)p.wd + beg, min(per, total - beg));
      } else if (c.lane == 0) {
        for (int t = 0; t < nT; t++) {
          mbar_wait(c.pub + 8 * t, 0);
          red_release(&p.cnt[(extra ? CNT_HX + mb1 + 2 * t : unit_of(role, t) < 10 ? CNT_AB : CNT_H + mb1) * 32]);
          TL(35 + t * 4);
        }
      }
    } else {
      if (!extra) {
        named_sync(3, 256 + 32);
        if (c.lane == 0) {
          red_release(&p.cnt[(CNT_XN + (blockIdx.x >> 3)) * 32]);
          TL(55);
          __nanosleep(5000);
          wait_counter<300>(&p.cnt[CNT_AB * 32], 160);         fence_proxy_async_global(); mbar_arrive(c.flagb);
          wait_counter<500>(&p.cnt[(CNT_H + mb2) * 32], 26);   fence_proxy_async_global(); mbar_arrive(c.flagb + 8);
          wait_counter<500>(&p.cnt[(CNT_HX + mb2) * 32], 1);   fence_proxy_async_global(); mbar_arrive(c.flagb + 16);
          if (atomicAdd(&p.cnt[CNT_DONE * 32], 1u) == 127u) {
            for (int i = 0; i < CNT_TOTAL; i++) p.cnt[i * 32] = 0;
          }
        }
      }
    }
  } else {
    asm volatile("barrier.cluster.arrive.relaxed.aligned;" ::: "memory");
    if (!extra) {
      const float sh = bf_lo(x0);
      float s = 0.f, ss = 0.f;
      #pragma unroll
      for (int i = 0; i < 5; i++) {
        const uint32_t w[4] = {v[i].x, v[i].y, v[i].z, v[i].w};
        #pragma unroll
        for (int j = 0; j < 4; j++) { const float a = bf_lo(w[j]) - sh, b = bf_hi(w[j]) - sh; s += a + b; ss = fmaf(a, a, ss); ss = fmaf(b, b, ss); }
      }
      #pragma unroll
      for (int o = 1; o < 16; o <<= 1) { s += __shfl_xor_sync(0xffffffffu, s, o); ss += __shfl_xor_sync(0xffffffffu, ss, o); }
      const float dm = s * (1.0f / D_);
      const float var = fmaxf(fmaf(-dm, dm, ss * (1.0f / D_)), 0.f);
      const float mb16 = round_bf(sh + dm);
      const float inv = __frcp_rn(round_bf(sqrtf(round_bf(round_bf(var) + 1e-5f))));
      uint4* dst = reinterpret_cast<uint4*>(p.xn + (size_t)xn_row(tok) * D_);
      #pragma unroll
      for (int i = 0; i < 5; i++) {
        uint32_t w[4] = {v[i].x, v[i].y, v[i].z, v[i].w};
        #pragma unroll
        for (int j = 0; j < 4; j++) {
          const uint32_t d = pack_bf16(bf_lo(w[j]) - mb16, bf_hi(w[j]) - mb16);
          w[j] = pack_bf16(bf_lo(d) * inv, bf_hi(d) * inv);
        }
        dst[l16 + 16 * i] = make_uint4(w[0], w[1], w[2], w[3]);
      }
      named_arrive(3, 256 + 32);
    }
    reg_alloc<232>();
    asm volatile("barrier.cluster.wait.acquire.aligned;" ::: "memory");
    if (threadIdx.x == 0) TL(54);

    const int rl = c.warp * 16 + (c.lane >> 2);
    const int nT1 = extra ? nT : nT - 1;
    #pragma unroll 1
    for (int t = c.wg; t < nT1; t += 2) {
      const int unit = extra ? 36 : unit_of(role, t);
      const int col = (extra ? mb1 + 2 * t : mb1) * 128 + (c.lane & 3) * 8;
      if (t > 0) named_sync(1 + c.wg, 256);
      const bool free_all = !extra && t == nT - 2;
      const bool has_next = t < nT - 1;
      float acc[2][64];
      if (unit < 10) {
        if (unit < 5) stage1_mma<0, false>(c, acc, t * 10, t == 0, has_next, free_all);
        else          stage1_mma<1, false>(c, acc, t * 10, t == 0, has_next, free_all);
        store_ab(acc, reinterpret_cast<uint4*>(p.abT + (size_t)(unit * 128 + rl) * S_ + col));
      } else {
        stage1_mma<2, false>(c, acc, t * 10, false, has_next, free_all);
        uint4* dst = reinterpret_cast<uint4*>(p.hT + (size_t)((unit - 10) * 64 + rl) * S_ + col);
        #pragma unroll
        for (int sl = 0; sl < 8; sl++) store_h_slice(acc, dst, sl);
      }
      publish(c, t);
    }

    if (!extra) {
      const size_t obase = (size_t)(mb2 * 128 + c.wg * 64 + rl) * D_ + nt * 160 + kh * 80 + (c.lane & 3) * 2;
      uint32_t xr[2][10];
      __nv_bfloat16* outw = p.out + (size_t)(mb2 * 128 + c.wg * 64 + c.warp * 16) * D_ + nt * 160;
      float acc[80];
      int i0 = 0;
      if (((nT - 1) & 1) == c.wg) {
        const int t = nT - 1;
        named_sync(1 + c.wg, 256);
        uint32_t gu[2][32];
        {
          float acc1[2][64];
          stage1_mma<2, true>(c, acc1, t * 10, false, true, false);
          #pragma unroll
          for (int r = 0; r < 32; r++) { gu[0][r] = pack_bf16(acc1[0][2 * r], acc1[0][2 * r + 1]); gu[1][r] = pack_bf16(acc1[1][2 * r], acc1[1][2 * r + 1]); }
        }
        #pragma unroll
        for (int r = 0; r < 80; r++) acc[r] = 0.f;
        uint4* dst = reinterpret_cast<uint4*>(p.hT + (size_t)((unit_of(role, t) - 10) * 64 + rl) * S_ + mb1 * 128 + (c.lane & 3) * 8);
        if (c.elect) TL(20 + c.wg);
        #pragma unroll
        for (int i = 0; i < 8; i++) {
          stage2_c(c, acc, i % R2, i / R2, i != 0);
          wgmma_wait<1>();
          if (i > 0) release2(c, (i - 1) % R2);
          uint32_t w[4];
          #pragma unroll
          for (int b = 0; b < 4; b++) {
            const int r = 8 * (i & 3) + 2 * b + (i >> 2);
            w[b] = pack_bf16(silu_mul(bf_lo(gu[0][r]), bf_lo(gu[1][r])), silu_mul(bf_hi(gu[0][r]), bf_hi(gu[1][r])));
          }
          dst[(i >> 2) * 8 * (S_ / 8) + (i & 3) * 4] = make_uint4(w[0], w[1], w[2], w[3]);
        }
        publish(c, t);
        wgmma_wait<0>();
        fence_acc(acc);
        i0 = 8;
      }
      #pragma unroll
      for (int hf = 0; hf < 2; hf++)
        #pragma unroll
        for (int j = 0; j < 10; j++) xr[hf][j] = __ldg(reinterpret_cast<const uint32_t*>(p.x + obase + hf * 8 * D_ + j * 8));
      if (i0 == 0) {
        #pragma unroll
        for (int r = 0; r < 80; r++) acc[r] = 0.f;
        named_sync(1 + c.wg, 256);
        if (c.elect) TL(20 + c.wg);
      }
      int slot = i0 % R2, ph = i0 / R2, prev = (i0 + R2 - 1) % R2;
      #pragma unroll 1
      for (int i = i0; i < nC; i++) {
        stage2_c(c, acc, slot, ph, i != 0);
        wgmma_wait<1>();
        if (i > 0) release2(c, prev);
        prev = slot;
        if (++slot == R2) { slot = 0; ph ^= 1; }
      }
      if (c.elect) TL(22 + c.wg);
      #pragma unroll 1
      for (int i = nC; i < n2; i++) {
        const uint32_t sa = DBASE + slot * (SLOT2 >> 4) + c.wg * 512 + LBO_NONE, sb = DBASE + slot * (SLOT2 >> 4) + (1024 + LBO_2K);
        mbar_wait(c.full2 + 8 * slot, ph);
        wgmma_fence();
        #pragma unroll
        for (int k = 0; k < 4; k++) wgmma_ss_n160<1, 1, 1>(acc, mk_desc(sa + k * 128, HI_SW128), mk_desc(sb + (k >> 1) * 640 + (k & 1) * 64, HI_SW64), 1);
        wgmma_commit();
        wgmma_wait<1>();
        if (i - 1 < n2 - R2) release2(c, prev);
        prev = slot;
        if (++slot == R2) { slot = 0; ph ^= 1; }
      }
      wgmma_wait<0>();
      fence_acc(acc);
      if (c.elect) TL(24 + c.wg);
      if (kh) stage2_finish<1>(c, acc, xr, outw);
      else    stage2_finish<0>(c, acc, xr, outw);

      if (c.elect) TL(28 + c.wg);
    }
  }
}

typedef CUresult (*PFN_encodeTiled)(CUtensorMap*, CUtensorMapDataType, cuuint32_t, void*, const cuuint64_t*, const cuuint64_t*,
                                    const cuuint32_t*, const cuuint32_t*, CUtensorMapInterleave, CUtensorMapSwizzle,
                                    CUtensorMapL2promotion, CUtensorMapFloatOOBfill);

void make_map(PFN_encodeTiled enc, CUtensorMap* m, const void* ptr, uint64_t rows, uint64_t cols, uint32_t box_rows, uint32_t box_cols, CUtensorMapSwizzle sw) {
  cuuint64_t dims[2] = {cols, rows};
  cuuint64_t strides[1] = {cols * 2};
  cuuint32_t box[2] = {box_cols, box_rows};
  cuuint32_t es[2] = {1, 1};
  enc(m, CU_TENSOR_MAP_DATA_TYPE_BFLOAT16, 2, const_cast<void*>(ptr), dims, strides, box, es, CU_TENSOR_MAP_INTERLEAVE_NONE, sw,
      CU_TENSOR_MAP_L2_PROMOTION_L2_256B, CU_TENSOR_MAP_FLOAT_OOB_FILL_NONE);
}
void make_map3(PFN_encodeTiled enc, CUtensorMap* m, const void* ptr, uint64_t rows, uint64_t cols, uint32_t box_rows, uint32_t box_cols, uint32_t nblk, CUtensorMapSwizzle sw) {
  cuuint64_t dims[3] = {box_cols, rows, cols / box_cols};
  cuuint64_t strides[2] = {cols * 2, (cuuint64_t)box_cols * 2};
  cuuint32_t box[3] = {box_cols, box_rows, nblk};
  cuuint32_t es[3] = {1, 1, 1};
  enc(m, CU_TENSOR_MAP_DATA_TYPE_BFLOAT16, 3, const_cast<void*>(ptr), dims, strides, box, es, CU_TENSOR_MAP_INTERLEAVE_NONE, sw,
      CU_TENSOR_MAP_L2_PROMOTION_L2_256B, CU_TENSOR_MAP_FLOAT_OOB_FILL_NONE);
}

}

extern "C" void kernel_launch(void* const* d_in, const int* in_sizes, int n_in, void* d_out, int out_size) {
  (void)in_sizes; (void)n_in; (void)out_size;
  PFN_encodeTiled enc = nullptr;
  cudaDriverEntryPointQueryResult qres;
  cudaGetDriverEntryPoint("cuTensorMapEncodeTiled", (void**)&enc, cudaEnableDefault, &qres);
  Params p;
  p.x = (const __nv_bfloat16*)d_in[0]; p.out = (__nv_bfloat16*)d_out;
  cudaGetSymbolAddress((void**)&p.xn, g_xn); cudaGetSymbolAddress((void**)&p.cnt, g_cnt);
  cudaGetSymbolAddress((void**)&p.abT, g_abT); cudaGetSymbolAddress((void**)&p.hT, g_hT);
  p.dr = (const __nv_bfloat16*)d_in[3]; p.di = (const __nv_bfloat16*)d_in[4];
  p.wg = (const __nv_bfloat16*)d_in[6]; p.wu = (const __nv_bfloat16*)d_in[7]; p.wd = (const __nv_bfloat16*)d_in[8];
  Maps maps;
  make_map(enc, &maps.xn, p.xn, S_, D_, 128, 64, CU_TENSOR_MAP_SWIZZLE_128B);
  make_map(enc, &maps.dr, d_in[3], D_, D_, 128, 64, CU_TENSOR_MAP_SWIZZLE_128B);
  make_map(enc, &maps.di, d_in[4], D_, D_, 128, 64, CU_TENSOR_MAP_SWIZZLE_128B);
  make_map(enc, &maps.wg, d_in[6], D_, F_, 64, 64, CU_TENSOR_MAP_SWIZZLE_128B);
  make_map(enc, &maps.wu, d_in[7], D_, F_, 64, 64, CU_TENSOR_MAP_SWIZZLE_128B);
  make_map(enc, &maps.cr, d_in[1], S_, S_, 128, 64, CU_TENSOR_MAP_SWIZZLE_128B);
  make_map(enc, &maps.ci, d_in[2], S_, S_, 128, 64, CU_TENSOR_MAP_SWIZZLE_128B);
  make_map3(enc, &maps.h, p.hT, F_, S_, 64, 64, 2, CU_TENSOR_MAP_SWIZZLE_128B);
  make_map(enc, &maps.ab, p.abT, 2 * D_, S_, 80, 64, CU_TENSOR_MAP_SWIZZLE_128B);
  make_map3(enc, &maps.wd, d_in[8], F_, D_, 32, 32, 5, CU_TENSOR_MAP_SWIZZLE_64B);
  cudaFuncSetAttribute(fused_kernel, cudaFuncAttributeMaxDynamicSharedMemorySize, SMEM_BYTES);
  cudaLaunchConfig_t cfg = {};
  cfg.gridDim = dim3(NUM_CTAS); cfg.blockDim = dim3(384); cfg.dynamicSmemBytes = SMEM_BYTES; cfg.stream = cudaStreamPerThread;
  cudaLaunchAttribute at[1];
  at[0].id = cudaLaunchAttributeClusterDimension; at[0].val.clusterDim.x = 2; at[0].val.clusterDim.y = 1; at[0].val.clusterDim.z = 1;
  cfg.attrs = at; cfg.numAttrs = 1;
  cudaLaunchKernelEx(&cfg, fused_kernel, p, maps);
}
```

```cpp
#include <cuda_runtime.h>
#include <cuda_bf16.h>
#include <cuda.h>
#include <stdint.h>

template<int TA, int TB, int SA> __device__ __forceinline__ void wgmma_ss_n80(float (&d)[40], uint64_t da, uint64_t db, int sd) {
  asm volatile("{\n.reg .pred p;\nsetp.ne.b32 p, %42, 0;\n"
    "wgmma.mma_async.sync.aligned.m64n80k16.f32.bf16.bf16 {%0, %1, %2, %3, %4, %5, %6, %7, %8, %9, %10, %11, %12, %13, %14, %15, %16, %17, %18, %19, %20, %21, %22, %23, %24, %25, %26, %27, %28, %29, %30, %31, %32, %33, %34, %35, %36, %37, %38, %39}, %40, %41, p, %45, 1, %43, %44;\n}\n"
    : "+f"(d[0]), "+f"(d[1]), "+f"(d[2]), "+f"(d[3]), "+f"(d[4]), "+f"(d[5]), "+f"(d[6]), "+f"(d[7]), "+f"(d[8]), "+f"(d[9]), "+f"(d[10]), "+f"(d[11]), "+f"(d[12]), "+f"(d[13]), "+f"(d[14]), "+f"(d[15]), "+f"(d[16]), "+f"(d[17]), "+f"(d[18]), "+f"(d[19]), "+f"(d[20]), "+f"(d[21]), "+f"(d[22]), "+f"(d[23]), "+f"(d[24]), "+f"(d[25]), "+f"(d[26]), "+f"(d[27]), "+f"(d[28]), "+f"(d[29]), "+f"(d[30]), "+f"(d[31]), "+f"(d[32]), "+f"(d[33]), "+f"(d[34]), "+f"(d[35]), "+f"(d[36]), "+f"(d[37]), "+f"(d[38]), "+f"(d[39])
    : "l"(da), "l"(db), "r"(sd), "n"(TA), "n"(TB), "n"(SA));
}
template<int TA, int TB, int SA> __device__ __forceinline__ void wgmma_ss_n128(float (&d)[64], uint64_t da, uint64_t db, int sd) {
  asm volatile("{\n.reg .pred p;\nsetp.ne.b32 p, %66, 0;\n"
    "wgmma.mma_async.sync.aligned.m64n128k16.f32.bf16.bf16 {%0, %1, %2, %3, %4, %5, %6, %7, %8, %9, %10, %11, %12, %13, %14, %15, %16, %17, %18, %19, %20, %21, %22, %23, %24, %25, %26, %27, %28, %29, %30, %31, %32, %33, %34, %35, %36, %37, %38, %39, %40, %41, %42, %43, %44, %45, %46, %47, %48, %49, %50, %51, %52, %53, %54, %55, %56, %57, %58, %59, %60, %61, %62, %63}, %64, %65, p, %69, 1, %67, %68;\n}\n"
    : "+f"(d[0]), "+f"(d[1]), "+f"(d[2]), "+f"(d[3]), "+f"(d[4]), "+f"(d[5]), "+f"(d[6]), "+f"(d[7]), "+f"(d[8]), "+f"(d[9]), "+f"(d[10]), "+f"(d[11]), "+f"(d[12]), "+f"(d[13]), "+f"(d[14]), "+f"(d[15]), "+f"(d[16]), "+f"(d[17]), "+f"(d[18]), "+f"(d[19]), "+f"(d[20]), "+f"(d[21]), "+f"(d[22]), "+f"(d[23]), "+f"(d[24]), "+f"(d[25]), "+f"(d[26]), "+f"(d[27]), "+f"(d[28]), "+f"(d[29]), "+f"(d[30]), "+f"(d[31]), "+f"(d[32]), "+f"(d[33]), "+f"(d[34]), "+f"(d[35]), "+f"(d[36]), "+f"(d[37]), "+f"(d[38]), "+f"(d[39]), "+f"(d[40]), "+f"(d[41]), "+f"(d[42]), "+f"(d[43]), "+f"(d[44]), "+f"(d[45]), "+f"(d[46]), "+f"(d[47]), "+f"(d[48]), "+f"(d[49]), "+f"(d[50]), "+f"(d[51]), "+f"(d[52]), "+f"(d[53]), "+f"(d[54]), "+f"(d[55]), "+f"(d[56]), "+f"(d[57]), "+f"(d[58]), "+f"(d[59]), "+f"(d[60]), "+f"(d[61]), "+f"(d[62]), "+f"(d[63])
    : "l"(da), "l"(db), "r"(sd), "n"(TA), "n"(TB), "n"(SA));
}
template<int TA, int TB, int SA> __device__ __forceinline__ void wgmma_ss_n160(float (&d)[80], uint64_t da, uint64_t db, int sd) {
  asm volatile("{\n.reg .pred p;\nsetp.ne.b32 p, %82, 0;\n"
    "wgmma.mma_async.sync.aligned.m64n160k16.f32.bf16.bf16 {%0, %1, %2, %3, %4, %5, %6, %7, %8, %9, %10, %11, %12, %13, %14, %15, %16, %17, %18, %19, %20, %21, %22, %23, %24, %25, %26, %27, %28, %29, %30, %31, %32, %33, %34, %35, %36, %37, %38, %39, %40, %41, %42, %43, %44, %45, %46, %47, %48, %49, %50, %51, %52, %53, %54, %55, %56, %57, %58, %59, %60, %61, %62, %63, %64, %65, %66, %67, %68, %69, %70, %71, %72, %73, %74, %75, %76, %77, %78, %79}, %80, %81, p, %85, 1, %83, %84;\n}\n"
    : "+f"(d[0]), "+f"(d[1]), "+f"(d[2]), "+f"(d[3]), "+f"(d[4]), "+f"(d[5]), "+f"(d[6]), "+f"(d[7]), "+f"(d[8]), "+f"(d[9]), "+f"(d[10]), "+f"(d[11]), "+f"(d[12]), "+f"(d[13]), "+f"(d[14]), "+f"(d[15]), "+f"(d[16]), "+f"(d[17]), "+f"(d[18]), "+f"(d[19]), "+f"(d[20]), "+f"(d[21]), "+f"(d[22]), "+f"(d[23]), "+f"(d[24]), "+f"(d[25]), "+f"(d[26]), "+f"(d[27]), "+f"(d[28]), "+f"(d[29]), "+f"(d[30]), "+f"(d[31]), "+f"(d[32]), "+f"(d[33]), "+f"(d[34]), "+f"(d[35]), "+f"(d[36]), "+f"(d[37]), "+f"(d[38]), "+f"(d[39]), "+f"(d[40]), "+f"(d[41]), "+f"(d[42]), "+f"(d[43]), "+f"(d[44]), "+f"(d[45]), "+f"(d[46]), "+f"(d[47]), "+f"(d[48]), "+f"(d[49]), "+f"(d[50]), "+f"(d[51]), "+f"(d[52]), "+f"(d[53]), "+f"(d[54]), "+f"(d[55]), "+f"(d[56]), "+f"(d[57]), "+f"(d[58]), "+f"(d[59]), "+f"(d[60]), "+f"(d[61]), "+f"(d[62]), "+f"(d[63]), "+f"(d[64]), "+f"(d[65]), "+f"(d[66]), "+f"(d[67]), "+f"(d[68]), "+f"(d[69]), "+f"(d[70]), "+f"(d[71]), "+f"(d[72]), "+f"(d[73]), "+f"(d[74]), "+f"(d[75]), "+f"(d[76]), "+f"(d[77]), "+f"(d[78]), "+f"(d[79])
    : "l"(da), "l"(db), "r"(sd), "n"(TA), "n"(TB), "n"(SA));
}

namespace {

constexpr int S_ = 2048, D_ = 640, F_ = 1728;
constexpr int A_CHUNK   = 16384;
constexpr int RING1_OFF = 10 * A_CHUNK;
constexpr int R1        = 4;
constexpr int SLOT2     = 36864;
constexpr int R2        = 6;
constexpr int BAR_OFF   = RING1_OFF + R1 * 16384;
constexpr int TL_OFF    = BAR_OFF + 512;
constexpr int SMEM_BYTES = TL_OFF + 512;
constexpr int NUM_CTAS  = 132;
#define NC1 37
#define ND1 13
#define MAPV 0
#define REL1 0
#define REL2 0
#define FREE0 3
#define ZERO_NS 5000
#define PFKB 7
#define STAG 5
#define EARLYWG 0
#define KHA 1
#define PF 0

__device__ __nv_bfloat16 g_xn[S_ * D_];
__device__ __nv_bfloat16 g_abT[2 * D_ * S_];
__device__ __nv_bfloat16 g_hT[F_ * S_];
constexpr int CNT_XN = 0, CNT_H = 16, CNT_HX = 32, CNT_A = 48, CNT_B = 49, CNT_DONE = 50, CNT_TOTAL = 51;
__device__ unsigned g_cnt[CNT_TOTAL * 32];
#define TL(idx) do {} while (0)

struct Params {
  const __nv_bfloat16* x; __nv_bfloat16* out;
  __nv_bfloat16* xn; unsigned* cnt; __nv_bfloat16* abT; __nv_bfloat16* hT;
  const __nv_bfloat16 *dr, *di, *wg, *wu, *wd;
};
struct Maps {
  CUtensorMap xn, dr, di, wg, wu, cr, ci, h, ab, wd;
};

__device__ __forceinline__ uint32_t smem_u32(const void* p) { return (uint32_t)__cvta_generic_to_shared(p); }
__device__ __forceinline__ void mbar_init(uint32_t bar, uint32_t count) { asm volatile("mbarrier.init.shared::cta.b64 [%0], %1;" :: "r"(bar), "r"(count)); }
__device__ __forceinline__ void mbar_expect_tx(uint32_t bar, uint32_t bytes) { asm volatile("mbarrier.arrive.expect_tx.shared::cta.b64 _, [%0], %1;" :: "r"(bar), "r"(bytes) : "memory"); }
__device__ __forceinline__ void mbar_arrive(uint32_t bar) { asm volatile("mbarrier.arrive.shared::cta.b64 _, [%0];" :: "r"(bar) : "memory"); }
__device__ __forceinline__ void mbar_arrive_cta(uint32_t bar, uint32_t cta) {
  asm volatile("{\n.reg .b32 ra;\nmapa.shared::cluster.u32 ra, %0, %1;\nmbarrier.arrive.shared::cluster.b64 _, [ra];\n}\n" :: "r"(bar), "r"(cta) : "memory");
}
__device__ __forceinline__ void mbar_wait(uint32_t bar, uint32_t parity) {
  asm volatile("{\n.reg .pred p;\n.reg .u32 n;\nmov.u32 n, 0;\n"
    "LAB_WAIT:\n"
    "mbarrier.try_wait.parity.shared::cta.b64 p, [%0], %1;\n"
    "@p bra LAB_DONE;\n"
    "add.u32 n, n, 1;\n"
    "setp.lt.u32 p, n, 4000000;\n"
    "@p bra LAB_WAIT;\n"
    "trap;\n"
    "LAB_DONE:\n}\n" :: "r"(bar), "r"(parity) : "memory");
}
__device__ __forceinline__ void tma_load(uint32_t dst, const CUtensorMap* map, int c0, int c1, uint32_t bar) {
  asm volatile("cp.async.bulk.tensor.2d.shared::cluster.global.mbarrier::complete_tx::bytes [%0], [%1, {%3, %4}], [%2];"
    :: "r"(dst), "l"(map), "r"(bar), "r"(c0), "r"(c1) : "memory");
}
__device__ __forceinline__ void tma_load_mc(uint32_t dst, const CUtensorMap* map, int c0, int c1, uint32_t bar) {
  asm volatile("cp.async.bulk.tensor.2d.shared::cluster.global.mbarrier::complete_tx::bytes.multicast::cluster [%0], [%1, {%3, %4}], [%2], %5;"
    :: "r"(dst), "l"(map), "r"(bar), "r"(c0), "r"(c1), "h"((uint16_t)3) : "memory");
}
__device__ __forceinline__ void tma_load_3d(uint32_t dst, const CUtensorMap* map, int c1, int c2, uint32_t bar) {
  asm volatile("cp.async.bulk.tensor.3d.shared::cluster.global.mbarrier::complete_tx::bytes [%0], [%1, {%5, %3, %4}], [%2];"
    :: "r"(dst), "l"(map), "r"(bar), "r"(c1), "r"(c2), "r"(0) : "memory");
}
__device__ __forceinline__ void tma_load_3d_mc(uint32_t dst, const CUtensorMap* map, int c1, int c2, uint32_t bar) {
  asm volatile("cp.async.bulk.tensor.3d.shared::cluster.global.mbarrier::complete_tx::bytes.multicast::cluster [%0], [%1, {%5, %3, %4}], [%2], %6;"
    :: "r"(dst), "l"(map), "r"(bar), "r"(c1), "r"(c2), "r"(0), "h"((uint16_t)3) : "memory");
}
__device__ __forceinline__ void tma_prefetch(const CUtensorMap* map, int c0, int c1) {
  asm volatile("cp.async.bulk.prefetch.tensor.2d.L2.global [%0, {%1, %2}];" :: "l"(map), "r"(c0), "r"(c1) : "memory");
}
__device__ __forceinline__ void prefetch_map(const CUtensorMap* map) { asm volatile("prefetch.tensormap [%0];" :: "l"(map) : "memory"); }
__device__ __forceinline__ void l2_prefetch(const void* p, uint32_t bytes) { asm volatile("cp.async.bulk.prefetch.L2.global [%0], %1;" :: "l"(p), "r"(bytes) : "memory"); }
__device__ __forceinline__ void wgmma_fence() { asm volatile("wgmma.fence.sync.aligned;" ::: "memory"); }
__device__ __forceinline__ void wgmma_commit() { asm volatile("wgmma.commit_group.sync.aligned;" ::: "memory"); }
template<int N> __device__ __forceinline__ void wgmma_wait() { asm volatile("wgmma.wait_group.sync.aligned %0;" :: "n"(N) : "memory"); }
template<int N> __device__ __forceinline__ void fence_acc(float (&d)[N]) {
  #pragma unroll
  for (int i = 0; i < N; i++) asm volatile("" : "+f"(d[i]) :: "memory");
}
__device__ __forceinline__ void named_sync(int id, int n) { asm volatile("bar.sync %0, %1;" :: "r"(id), "r"(n) : "memory"); }
__device__ __forceinline__ void named_arrive(int id, int n) { asm volatile("bar.arrive %0, %1;" :: "r"(id), "r"(n) : "memory"); }
template<int R> __device__ __forceinline__ void reg_alloc() { asm volatile("setmaxnreg.inc.sync.aligned.u32 %0;" :: "n"(R)); }
template<int R> __device__ __forceinline__ void reg_dealloc() { asm volatile("setmaxnreg.dec.sync.aligned.u32 %0;" :: "n"(R)); }
__device__ __forceinline__ void fence_proxy_async_global() { asm volatile("fence.proxy.async.global;" ::: "memory"); }
__device__ __forceinline__ void red_release(unsigned* p) { asm volatile("red.release.gpu.global.add.u32 [%0], 1;" :: "l"(p) : "memory"); }
template<int SLEEP_NS>
__device__ __forceinline__ void wait_counter(const unsigned* p, unsigned target) {
  asm volatile("{\n.reg .pred p;\n.reg .u32 n, v;\nmov.u32 n, 0;\n"
    "LAB_WAIT:\n"
    "ld.acquire.gpu.global.u32 v, [%0];\n"
    "setp.ge.u32 p, v, %1;\n"
    "@p bra LAB_DONE;\n"
    "nanosleep.u32 %2;\n"
    "add.u32 n, n, 1;\n"
    "setp.lt.u32 p, n, 2000000;\n"
    "@p bra LAB_WAIT;\n"
    "trap;\n"
    "LAB_DONE:\n}\n" :: "l"(p), "r"(target), "n"(SLEEP_NS) : "memory");
}
constexpr uint32_t HI_SW128 = (1024 >> 4) | (1u << 30);
constexpr uint32_t HI_SW64  = (512 >> 4) | (2u << 30);
constexpr uint32_t DBASE    = 0x400 >> 4;
constexpr uint32_t LBO_NONE = 1u << 16;
constexpr uint32_t LBO_2K   = (2048u >> 4) << 16;
__device__ __forceinline__ uint64_t mk_desc(uint32_t lo, uint32_t hi) { uint64_t d; asm("mov.b64 %0, {%1, %2};" : "=l"(d) : "r"(lo), "r"(hi)); return d; }

__device__ __forceinline__ uint32_t pack_bf16(float lo, float hi) {
  uint32_t r; asm("cvt.rn.bf16x2.f32 %0, %1, %2;" : "=r"(r) : "f"(hi), "f"(lo)); return r;
}
__device__ __forceinline__ float bf_lo(uint32_t v) { return __uint_as_float(v << 16); }
__device__ __forceinline__ float bf_hi(uint32_t v) { return __uint_as_float(v & 0xffff0000u); }
__device__ __forceinline__ float round_bf(float v) { return bf_lo(pack_bf16(v, 0.f)); }
__device__ __forceinline__ uint32_t norm2(uint32_t x, uint32_t m2, uint32_t ih2, uint32_t il2) {
  uint32_t d, t, r;
  asm("sub.rn.bf16x2 %0, %1, %2;" : "=r"(d) : "r"(x), "r"(m2));
  asm("mul.rn.bf16x2 %0, %1, %2;" : "=r"(t) : "r"(d), "r"(il2));
  asm("fma.rn.bf16x2 %0, %1, %2, %3;" : "=r"(r) : "r"(d), "r"(ih2), "r"(t));
  return r;
}
__device__ __forceinline__ float silu_mul(float g, float u) {
  float e, r;
  asm("ex2.approx.ftz.f32 %0, %1;" : "=f"(e) : "f"(g * -1.4426950408889634f));
  asm("rcp.approx.ftz.f32 %0, %1;" : "=f"(r) : "f"(e + 1.0f));
  return (g * u) * r;
}
__device__ __forceinline__ int xn_row(int t) { return (t & ~30) | ((t & 6) << 2) | ((t & 24) >> 2); }
__device__ __forceinline__ int unit_of(int role, int t) {
  const int two_ab = (role & 5) == 0;
  if (t == 0) return role;
  if (t == 1 && two_ab) return 8 + (role >> 1);
  return 9 + 3 * role + (role > 4) + (role > 6) + t - two_ab;
}

__device__ __forceinline__ void prefetch_unit(const Maps& maps, int unit, int kb) {
  if (unit < 10) tma_prefetch(unit < 5 ? &maps.dr : &maps.di, kb * 64, (unit < 5 ? unit : unit - 5) * 128);
  else { tma_prefetch(&maps.wg, (unit - 10) * 64, kb * 64); tma_prefetch(&maps.wu, (unit - 10) * 64, kb * 64); }
}

struct Ctx {
  uint32_t sbase, full1, empty1, full2, empty2, flagb, pub, xfull;
  int wg, warp, lane, zero;
  bool elect;
};

template<int MODE, bool LAST>
__device__ __forceinline__ void stage1_mma(const Ctx& c, float (&acc)[2][64], int it0, bool first, bool has_next, bool free_all) {
  int prev = 0;
  #pragma unroll 1
  for (int kb = 0; kb < 10; kb++) {
    const int it = it0 + kb;
    const int slot = it & 3;
    const uint32_t bx = DBASE + kb * (A_CHUNK >> 4) + LBO_NONE;
    const uint32_t ar = DBASE + slot * 1024 + ((RING1_OFF >> 4) + LBO_NONE);
    if (MODE != 2 && first) mbar_wait(c.xfull + 8 * kb, 0);
    mbar_wait(c.full1 + 8 * slot, (it >> 2) & 1);
    if (kb == 9 && has_next) named_arrive(1 + (c.wg ^ 1), 256);
    wgmma_fence();
    #pragma unroll
    for (int k = 0; k < 4; k++) {
      #pragma unroll
      for (int i = 0; i < 2; i++) {
        if (MODE == 2) wgmma_ss_n128<1, 0, 1>(acc[i], mk_desc(ar + i * 512 + k * 128, HI_SW128), mk_desc(bx + k * 2, HI_SW128), (kb | k) != 0);
        else           wgmma_ss_n128<0, 0, (MODE == 1 ? -1 : 1)>(acc[i], mk_desc(ar + i * 512 + k * 2, HI_SW128), mk_desc(bx + k * 2, HI_SW128), (kb | k) != 0);
      }
      if (k == REL1) {
        wgmma_commit();
        wgmma_wait<1>();
        if (kb > 0 && c.elect) {
          mbar_arrive(c.empty1 + 8 * prev);
          if (LAST && kb >= FREE0) {
            const int j = kb - FREE0;
            if (FREE0 == 3 ? (kb & 1) : true) {
              const uint32_t b = c.empty2 + 8 * (FREE0 == 3 ? (j >> 1) : j);
              mbar_arrive_cta(b, 0); mbar_arrive_cta(b, 1);
            }
          }
        }
        if (k < 3) wgmma_fence();
      }
    }
    if (REL1 < 3) wgmma_commit();
    prev = slot;
  }
  #pragma unroll 1
  for (int z = c.zero; z < 1; z++) {
    wgmma_wait<0>();
    if (c.elect) {
      mbar_arrive(c.empty1 + 8 * prev);
      TL(33 + (it0 / 10) * 4);
      if (LAST || free_all) {
        #pragma unroll
        for (int j = LAST ? 4 : 0; j < R2; j++) { mbar_arrive_cta(c.empty2 + 8 * j, 0); mbar_arrive_cta(c.empty2 + 8 * j, 1); }
      }
    }
  }
  wgmma_wait<0>();
  fence_acc(acc[0]); fence_acc(acc[1]);
}
__device__ __forceinline__ void store_ab(const float (&acc)[2][64], uint4* dst) {
  #pragma unroll
  for (int i = 0; i < 2; i++)
    #pragma unroll
    for (int hf = 0; hf < 2; hf++)
      #pragma unroll
      for (int J = 0; J < 4; J++) {
        const int r = 16 * J + 2 * hf;
        dst[(i * 64 + hf * 8) * (S_ / 8) + J * 4] = make_uint4(pack_bf16(acc[i][r], acc[i][r + 1]), pack_bf16(acc[i][r + 4], acc[i][r + 5]),
                                                               pack_bf16(acc[i][r + 8], acc[i][r + 9]), pack_bf16(acc[i][r + 12], acc[i][r + 13]));
      }
}
__device__ __forceinline__ void store_h_slice(const float (&acc)[2][64], uint4* dst, int sl) {
  const int hf = sl >> 2, J = sl & 3;
  uint32_t w[4];
  #pragma unroll
  for (int b = 0; b < 4; b++) {
    const int r = 16 * J + 4 * b + 2 * hf;
    w[b] = pack_bf16(silu_mul(acc[0][r], acc[1][r]), silu_mul(acc[0][r + 1], acc[1][r + 1]));
  }
  dst[hf * 8 * (S_ / 8) + J * 4] = make_uint4(w[0], w[1], w[2], w[3]);
}
__device__ __forceinline__ void publish(const Ctx& c, int t) {
  if (c.elect) TL(34 + t * 4);
  __syncwarp();
  if (c.lane == 0) mbar_arrive(c.pub + 8 * t);
}
__device__ __forceinline__ void release2(const Ctx& c, int slot) {
  if (c.elect) { mbar_arrive_cta(c.empty2 + 8 * slot, 0); mbar_arrive_cta(c.empty2 + 8 * slot, 1); }
}
template<bool DPART>
__device__ __forceinline__ void stage2_kb(const Ctx& c, float (&acc)[80], int slot, int ph, int prev, bool rel) {
  const uint32_t sa = DBASE + slot * (SLOT2 >> 4) + c.wg * 512 + LBO_NONE, sb = DBASE + slot * (SLOT2 >> 4) + (1024 + (DPART ? LBO_2K : LBO_NONE));
  mbar_wait(c.full2 + 8 * slot, ph);
  wgmma_fence();
  #pragma unroll
  for (int k = 0; k < 4; k++) {
    if (DPART) wgmma_ss_n160<1, 1, 1>(acc, mk_desc(sa + k * 128, HI_SW128), mk_desc(sb + (k >> 1) * 640 + (k & 1) * 64, HI_SW64), 1);
    else       wgmma_ss_n160<0, 0, 1>(acc, mk_desc(sa + k * 2, HI_SW128), mk_desc(sb + k * 2, HI_SW128), 1);
    if (k == REL2) {
      wgmma_commit();
      wgmma_wait<1>();
      if (rel) release2(c, prev);
      if (k < 3) wgmma_fence();
    }
  }
  if (REL2 < 3) wgmma_commit();
}

template<int KH>
__device__ __forceinline__ void stage2_finish(const Ctx& c, float (&acc)[80], const uint32_t (&xr)[2][10], __nv_bfloat16* outw) {
  #pragma unroll
  for (int j = 0; j < 10; j++) {
    acc[KH * 40 + 4 * j] += bf_lo(xr[0][j]); acc[KH * 40 + 4 * j + 1] += bf_hi(xr[0][j]);
    acc[KH * 40 + 4 * j + 2] += bf_lo(xr[1][j]); acc[KH * 40 + 4 * j + 3] += bf_hi(xr[1][j]);
  }
  const uint32_t stg = c.sbase + c.warp * SLOT2 + c.wg * 8192;
  const uint32_t sw = stg + (c.lane & 15) * 336 + (c.lane >> 4) * 16;
  #pragma unroll
  for (int jj = 0; jj < 10; jj++) {
    asm volatile("stmatrix.sync.aligned.m8n8.x4.shared.b16 [%0], {%1, %2, %3, %4};" :: "r"(sw + jj * 32),
                 "r"(pack_bf16(acc[8 * jj], acc[8 * jj + 1])), "r"(pack_bf16(acc[8 * jj + 2], acc[8 * jj + 3])),
                 "r"(pack_bf16(acc[8 * jj + 4], acc[8 * jj + 5])), "r"(pack_bf16(acc[8 * jj + 6], acc[8 * jj + 7])) : "memory");
  }
  __syncwarp();
  uint4 v[10];
  #pragma unroll
  for (int i = 0; i < 10; i++) {
    const int idx = i * 32 + c.lane, row = idx / 20, ch = idx - row * 20;
    asm volatile("ld.shared.v4.u32 {%0, %1, %2, %3}, [%4];" : "=r"(v[i].x), "=r"(v[i].y), "=r"(v[i].z), "=r"(v[i].w) : "r"(stg + row * 336 + ch * 16) : "memory");
  }
  #pragma unroll
  for (int i = 0; i < 10; i++) {
    const int idx = i * 32 + c.lane, row = idx / 20, ch = idx - row * 20;
    asm volatile("red.global.add.noftz.v4.bf16x2 [%0], {%1, %2, %3, %4};" :: "l"(outw + row * D_ + ch * 8), "r"(v[i].x), "r"(v[i].y), "r"(v[i].z), "r"(v[i].w) : "memory");
  }
}

__global__ void __launch_bounds__(384, 1)
fused_kernel(const __grid_constant__ Params p, const __grid_constant__ Maps maps) {
  extern __shared__ __align__(1024) uint8_t smem_raw[];
  const int cl = blockIdx.x >> 1, rank = blockIdx.x & 1;
  const bool extra = cl >= 64;
  const int tok = (blockIdx.x & 127) * 16 + ((threadIdx.x >> 4) & 15), l16 = threadIdx.x & 15;
  uint4 v[5];
  uint32_t x0 = 0;
  if (threadIdx.x < 256) {
    const uint4* xs = reinterpret_cast<const uint4*>(p.x + (size_t)tok * D_);
    #pragma unroll
    for (int i = 0; i < 5; i++) v[i] = __ldg(xs + l16 + 16 * i);
    x0 = __ldg(reinterpret_cast<const uint32_t*>(xs));
  }
  int kh, nt, grp;
  if (cl >= 4 && cl < 36) { kh = KHA; grp = (cl - 4) & 7; nt = (cl - 4) >> 3; }
  else if (cl >= 36)      { kh = 1 - KHA; nt = (cl - 36) / 7; grp = 1 + (cl - 36) - nt * 7; nt &= 3; }
  else                    { kh = 1 - KHA; grp = 0; nt = cl; }
  const int mb2 = grp * 2 + rank;
  const int role = kh + 2 * ((nt & 1) * 2 + rank);
  const int mb1 = extra ? (cl - 64) * 8 + rank : grp * 2 + (nt >> 1);

  Ctx c;
  c.sbase = __shfl_sync(0xffffffffu, smem_u32(smem_raw), 0);
  c.zero = __shfl_sync(0xffffffffu, threadIdx.x >> 10, 0);
  c.full1 = c.sbase + BAR_OFF; c.empty1 = c.full1 + 8 * R1; c.full2 = c.empty1 + 8 * R1; c.empty2 = c.full2 + 8 * R2;
  c.flagb = c.empty2 + 8 * R2; c.pub = c.flagb + 8 * 4; c.xfull = c.pub + 8 * 5;
  c.wg = __shfl_sync(0xffffffffu, threadIdx.x >> 7, 0);
  c.warp = __shfl_sync(0xffffffffu, (threadIdx.x >> 5) & 3, 0);
  c.lane = threadIdx.x & 31;
  c.elect = (threadIdx.x & 127) == 0;

  const int nT = extra ? 4 : 5 - kh;
  const int nC = kh ? NC1 : 64 - NC1, c0 = kh ? 0 : NC1, nD = kh ? ND1 : 27 - ND1, d0 = kh ? 0 : ND1;
  const int n2 = nC + nD;

  if (c.wg == 2) {
    reg_dealloc<40>();
    int wlo = c.warp & 1, whi = c.warp >> 1;
    asm volatile("" : "+r"(wlo)); asm volatile("" : "+r"(whi));
    const bool w0 = !whi && !wlo, w1 = !whi && wlo, w2 = whi && !wlo;
    if (c.lane == 0) {
      if (w0) {
        #pragma unroll
        for (int i = 0; i < 2 * R1; i++) mbar_init(c.full1 + 8 * i, 1);
      } else if (w1) {
        prefetch_map(&maps.xn);
        #pragma unroll
        for (int i = 0; i < 10; i++) mbar_init(c.xfull + 8 * i, 1);
      } else if (w2) {
        #pragma unroll
        for (int i = 0; i < R2; i++) { mbar_init(c.full2 + 8 * i, 1); mbar_init(c.empty2 + 8 * i, 4); }
      } else {
        #pragma unroll
        for (int i = 0; i < 4; i++) mbar_init(c.flagb + 8 * i, 1);
        #pragma unroll
        for (int i = 0; i < 5; i++) mbar_init(c.pub + 8 * i, 4);
        if ((c.sbase & 0x3FFFFu) != 0x400u) asm volatile("trap;");
      }
      asm volatile("fence.mbarrier_init.release.cluster;" ::: "memory");
      if (w0) TL(11);
    }
    __syncwarp();
    asm volatile("barrier.cluster.arrive.relaxed.aligned;" ::: "memory");
    asm volatile("barrier.cluster.wait.acquire.aligned;" ::: "memory");
    if (w0) {
      if (c.lane == 0) {
        int it = 0;
        for (int t = 0; t < nT; t++) {
          const int unit = extra ? 36 : unit_of(role, t);
          for (int kb = 0; kb < 10; kb++, it++) {
            const int slot = it & 3;
            const uint32_t full = c.full1 + 8 * slot;
            const uint32_t dst = c.sbase + RING1_OFF + slot * 16384;
            mbar_wait(c.empty1 + 8 * slot, ((it >> 2) & 1) ^ 1);
            mbar_expect_tx(full, extra ? 32768 : 16384);
            if (unit < 10) {
              tma_load(dst, unit < 5 ? &maps.dr : &maps.di, kb * 64, (unit < 5 ? unit : unit - 5) * 128, full);
            } else {
              tma_load(dst, &maps.wg, (unit - 10) * 64, kb * 64, full);
              tma_load(dst + 8192, &maps.wu, (unit - 10) * 64, kb * 64, full);
            }
            if (it == 3) { TL(12); prefetch_map(&maps.wg); prefetch_map(&maps.wu); prefetch_map(&maps.di); }
            if (kb == PFKB && t + 2 < nT && !extra && mb1 < 10) prefetch_unit(maps, unit_of(role, t + 2), mb1);
            if (extra) {
              if (kb == 0) { wait_counter<100>(&p.cnt[(CNT_XN + mb1 + 2 * t) * 32], 8); fence_proxy_async_global(); }
              tma_load(c.sbase + kb * A_CHUNK, &maps.xn, kb * 64, (mb1 + 2 * t) * 128, full);
            }
          }
        }
      }
    } else if (w1) {
      if (c.lane == 0 && !extra) {
        #pragma unroll
        for (int i = 0; i < 10; i++) mbar_expect_tx(c.xfull + 8 * i, A_CHUNK);
        wait_counter<0>(&p.cnt[(CNT_XN + mb1) * 32], 8);
        fence_proxy_async_global();
        TL(1);
        #pragma unroll
        for (int i = 0; i < 5; i++) tma_load_mc(c.sbase + (2 * i + rank) * A_CHUNK, &maps.xn, (2 * i + rank) * 64, mb1 * 128, c.xfull + 8 * (2 * i + rank));
        TL(14);
        if (mb1 < 10) prefetch_unit(maps, unit_of(role, 1), mb1);
        prefetch_map(&maps.cr); prefetch_map(&maps.ci); prefetch_map(&maps.ab); prefetch_map(&maps.h); prefetch_map(&maps.wd);
        int slot = 0, ph = 0;
        for (int i = 0; i < n2; i++) {
          if (PF > 0 && ((i + PF) & 3) == nt && i + PF < nC) { const int kc = c0 + i + PF; tma_prefetch(kc >= 32 ? &maps.ci : &maps.cr, (kc & 31) * 64, mb2 * 128); }
          const uint32_t full = c.full2 + 8 * slot;
          const uint32_t dst = c.sbase + slot * SLOT2;
          mbar_wait(c.empty2 + 8 * slot, ph);
          if (i == 0) { TL(2); mbar_wait(c.flagb, 0); fence_proxy_async_global(); TL(3); }
          if (c0 + i == max(c0, 32)) { mbar_wait(c.flagb + 24, 0); fence_proxy_async_global(); }
          mbar_expect_tx(full, SLOT2);
          if (i < nC) {
            const int kc = c0 + i;
            const int im = kc >= 32;
            const int kk = (kc & 31) * 64;
            tma_load(dst, im ? &maps.ci : &maps.cr, kk, mb2 * 128, full);
            tma_load_mc(dst + 16384 + rank * 10240, &maps.ab, kk, im * 640 + nt * 160 + rank * 80, full);
          } else {
            const int kd = d0 + i - nC;
            tma_load_3d_mc(dst + 16384 + rank * 10240, &maps.wd, kd * 64 + rank * 32, nt * 5, full);
            if (i == nC) { TL(4); mbar_wait(c.flagb + 8, 0); fence_proxy_async_global(); TL(5); }
            if (kd == 26) { mbar_wait(c.flagb + 16, 0); fence_proxy_async_global(); }
            tma_load_3d(dst, &maps.h, kd * 64, mb2 * 2, full);
          }
          if (++slot == R2) { slot = 0; ph ^= 1; }
        }
      }
    } else if (w2) {
      const uint32_t total = D_ * F_ * 2, per = ((total + NUM_CTAS - 1) / NUM_CTAS + 127) & ~127u, beg = blockIdx.x * per;
      if (c.lane == 0 && !extra && mb1 < 6) prefetch_unit(maps, role, 4 + mb1);
      __nanosleep(ZERO_NS);
      if (!extra) {
        __nv_bfloat16* zb = p.out + (size_t)mb2 * 128 * D_ + nt * 160 + kh * 80;
        #pragma unroll 4
        for (int i = c.lane; i < 1280; i += 32) { const int r = i / 10; *reinterpret_cast<uint4*>(zb + r * D_ + (i - r * 10) * 8) = make_uint4(0u, 0u, 0u, 0u); }
      }
      __syncwarp();
      if (c.lane == 1) {
        __nanosleep(6000);
        if (beg < total) l2_prefetch((const char*)p.wd + beg, min(per, total - beg));
      } else if (c.lane == 0) {
        for (int t = 0; t < nT; t++) {
          mbar_wait(c.pub + 8 * t, 0);
          const int unit = unit_of(role, t);
          red_release(&p.cnt[(extra ? CNT_HX + mb1 + 2 * t : unit < 5 ? CNT_A : unit < 10 ? CNT_B : CNT_H + mb1) * 32]);
          TL(35 + t * 4);
        }
      }
    } else {
      if (!extra) {
        named_sync(3, 256 + 32);
        if (c.lane == 0) {
          red_release(&p.cnt[(CNT_XN + (blockIdx.x >> 3)) * 32]);
          TL(55);
          __nanosleep(5000);
          wait_counter<300>(&p.cnt[CNT_A * 32], 80);           fence_proxy_async_global(); mbar_arrive(c.flagb);
          wait_counter<300>(&p.cnt[CNT_B * 32], 80);           fence_proxy_async_global(); mbar_arrive(c.flagb + 24);
          wait_counter<500>(&p.cnt[(CNT_H + mb2) * 32], 26);   fence_proxy_async_global(); mbar_arrive(c.flagb + 8);
          wait_counter<500>(&p.cnt[(CNT_HX + mb2) * 32], 1);   fence_proxy_async_global(); mbar_arrive(c.flagb + 16);
          if (atomicAdd(&p.cnt[CNT_DONE * 32], 1u) == 127u) {
            for (int i = 0; i < CNT_TOTAL; i++) p.cnt[i * 32] = 0;
          }
        }
      }
    }
  } else {
    asm volatile("barrier.cluster.arrive.relaxed.aligned;" ::: "memory");
    if (!extra) {
      const float sh = bf_lo(x0);
      float s0 = 0.f, s1 = 0.f, q0 = 0.f, q1 = 0.f;
      #pragma unroll
      for (int i = 0; i < 5; i++) {
        const uint32_t w[4] = {v[i].x, v[i].y, v[i].z, v[i].w};
        #pragma unroll
        for (int j = 0; j < 4; j++) { const float a = bf_lo(w[j]) - sh, b = bf_hi(w[j]) - sh; s0 += a; s1 += b; q0 = fmaf(a, a, q0); q1 = fmaf(b, b, q1); }
      }
      float s = s0 + s1, ss = q0 + q1;
      #pragma unroll
      for (int o = 1; o < 16; o <<= 1) { s += __shfl_xor_sync(0xffffffffu, s, o); ss += __shfl_xor_sync(0xffffffffu, ss, o); }
      const float dm = s * (1.0f / D_);
      const float var = fmaxf(fmaf(-dm, dm, ss * (1.0f / D_)), 0.f);
      float sd, inv;
      asm("sqrt.approx.f32 %0, %1;" : "=f"(sd) : "f"(round_bf(round_bf(var) + 1e-5f)));
      asm("rcp.approx.f32 %0, %1;" : "=f"(inv) : "f"(round_bf(sd)));
      const float ih = round_bf(inv);
      const uint32_t m2 = pack_bf16(sh + dm, sh + dm), ih2 = pack_bf16(ih, ih), il2 = pack_bf16(inv - ih, inv - ih);
      uint4* dst = reinterpret_cast<uint4*>(p.xn + (size_t)xn_row(tok) * D_);
      #pragma unroll
      for (int i = 0; i < 5; i++)
        dst[l16 + 16 * i] = make_uint4(norm2(v[i].x, m2, ih2, il2), norm2(v[i].y, m2, ih2, il2), norm2(v[i].z, m2, ih2, il2), norm2(v[i].w, m2, ih2, il2));
      named_arrive(3, 256 + 32);
    }
    reg_alloc<232>();
    asm volatile("barrier.cluster.wait.acquire.aligned;" ::: "memory");
    if (threadIdx.x == 0) TL(54);

    const int rl = c.warp * 16 + (c.lane >> 2);
    const int nT1 = extra ? nT : nT - 1;
    #pragma unroll 1
    for (int t = c.wg; t < nT1; t += 2) {
      const int unit = extra ? 36 : unit_of(role, t);
      const int col = (extra ? mb1 + 2 * t : mb1) * 128 + (c.lane & 3) * 8;
      if (t > 0) named_sync(1 + c.wg, 256);
      const bool free_all = !extra && t == nT - 2;
      const bool has_next = t < nT - 1;
      float acc[2][64];
      if (unit < 10) {
        if (unit < 5) stage1_mma<0, false>(c, acc, t * 10, t == 0, has_next, free_all);
        else          stage1_mma<1, false>(c, acc, t * 10, t == 0, has_next, free_all);
        store_ab(acc, reinterpret_cast<uint4*>(p.abT + (size_t)(unit * 128 + rl) * S_ + col));
      } else {
        stage1_mma<2, false>(c, acc, t * 10, false, has_next, free_all);
        uint4* dst = reinterpret_cast<uint4*>(p.hT + (size_t)((unit - 10) * 64 + rl) * S_ + col);
        #pragma unroll
        for (int sl = 0; sl < 8; sl++) store_h_slice(acc, dst, sl);
      }
      publish(c, t);
    }

    if (!extra) {
      const size_t obase = (size_t)(mb2 * 128 + c.wg * 64 + rl) * D_ + nt * 160 + kh * 80 + (c.lane & 3) * 2;
      uint32_t xr[2][10];
      __nv_bfloat16* outw = p.out + (size_t)(mb2 * 128 + c.wg * 64 + c.warp * 16) * D_ + nt * 160;
      float acc[80];
      int i0 = 0;
      if (((nT - 1) & 1) == c.wg) {
        const int t = nT - 1;
        named_sync(1 + c.wg, 256);
        uint32_t gu[2][32];
        {
          float acc1[2][64];
          stage1_mma<2, true>(c, acc1, t * 10, false, true, false);
          #pragma unroll
          for (int r = 0; r < 32; r++) { gu[0][r] = pack_bf16(acc1[0][2 * r], acc1[0][2 * r + 1]); gu[1][r] = pack_bf16(acc1[1][2 * r], acc1[1][2 * r + 1]); }
        }
        #pragma unroll
        for (int r = 0; r < 80; r++) acc[r] = 0.f;
        uint4* dst = reinterpret_cast<uint4*>(p.hT + (size_t)((unit_of(role, t) - 10) * 64 + rl) * S_ + mb1 * 128 + (c.lane & 3) * 8);
        if (c.elect) TL(20 + c.wg);
        #pragma unroll
        for (int i = 0; i < 8; i++) {
          stage2_kb<false>(c, acc, i % R2, i / R2, (i + R2 - 1) % R2, i > 0);
          uint32_t w[4];
          #pragma unroll
          for (int b = 0; b < 4; b++) {
            const int r = 8 * (i & 3) + 2 * b + (i >> 2);
            w[b] = pack_bf16(silu_mul(bf_lo(gu[0][r]), bf_lo(gu[1][r])), silu_mul(bf_hi(gu[0][r]), bf_hi(gu[1][r])));
          }
          dst[(i >> 2) * 8 * (S_ / 8) + (i & 3) * 4] = make_uint4(w[0], w[1], w[2], w[3]);
        }
        publish(c, t);
        wgmma_wait<0>();
        fence_acc(acc);
        i0 = 8;
      }
      #pragma unroll
      for (int hf = 0; hf < 2; hf++)
        #pragma unroll
        for (int j = 0; j < 10; j++) xr[hf][j] = __ldg(reinterpret_cast<const uint32_t*>(p.x + obase + hf * 8 * D_ + j * 8));
      if (i0 == 0) {
        #pragma unroll
        for (int r = 0; r < 80; r++) acc[r] = 0.f;
        named_sync(1 + c.wg, 256);
        if (c.elect) TL(20 + c.wg);
      }
      int slot = i0 % R2, ph = i0 / R2, prev = (i0 + R2 - 1) % R2;
      #pragma unroll 1
      for (int i = i0; i < nC; i++) {
        stage2_kb<false>(c, acc, slot, ph, prev, i > 0);
        prev = slot;
        if (++slot == R2) { slot = 0; ph ^= 1; }
      }
      if (c.elect) TL(22 + c.wg);
      #pragma unroll 1
      for (int i = nC; i < n2; i++) {
        if (STAG > 0 && i == n2 - STAG && c.wg != EARLYWG) {
          wgmma_wait<0>();
          if (STAG == R2) release2(c, prev);
          named_sync(4, 256);
        }
        stage2_kb<true>(c, acc, slot, ph, prev, i - 1 < n2 - R2 && !(STAG == R2 && c.wg != EARLYWG && i == n2 - STAG));
        prev = slot;
        if (++slot == R2) { slot = 0; ph ^= 1; }
      }
      if (STAG > 0 && c.wg == EARLYWG) named_arrive(4, 256);
      wgmma_wait<0>();
      fence_acc(acc);
      if (c.elect) TL(24 + c.wg);
      if (kh) stage2_finish<1>(c, acc, xr, outw);
      else    stage2_finish<0>(c, acc, xr, outw);

      if (c.elect) TL(28 + c.wg);
    }
  }
}

typedef CUresult (*PFN_encodeTiled)(CUtensorMap*, CUtensorMapDataType, cuuint32_t, void*, const cuuint64_t*, const cuuint64_t*,
                                    const cuuint32_t*, const cuuint32_t*, CUtensorMapInterleave, CUtensorMapSwizzle,
                                    CUtensorMapL2promotion, CUtensorMapFloatOOBfill);

void make_map(PFN_encodeTiled enc, CUtensorMap* m, const void* ptr, uint64_t rows, uint64_t cols, uint32_t box_rows, uint32_t box_cols, CUtensorMapSwizzle sw) {
  cuuint64_t dims[2] = {cols, rows};
  cuuint64_t strides[1] = {cols * 2};
  cuuint32_t box[2] = {box_cols, box_rows};
  cuuint32_t es[2] = {1, 1};
  enc(m, CU_TENSOR_MAP_DATA_TYPE_BFLOAT16, 2, const_cast<void*>(ptr), dims, strides, box, es, CU_TENSOR_MAP_INTERLEAVE_NONE, sw,
      CU_TENSOR_MAP_L2_PROMOTION_L2_256B, CU_TENSOR_MAP_FLOAT_OOB_FILL_NONE);
}
void make_map3(PFN_encodeTiled enc, CUtensorMap* m, const void* ptr, uint64_t rows, uint64_t cols, uint32_t box_rows, uint32_t box_cols, uint32_t nblk, CUtensorMapSwizzle sw) {
  cuuint64_t dims[3] = {box_cols, rows, cols / box_cols};
  cuuint64_t strides[2] = {cols * 2, (cuuint64_t)box_cols * 2};
  cuuint32_t box[3] = {box_cols, box_rows, nblk};
  cuuint32_t es[3] = {1, 1, 1};
  enc(m, CU_TENSOR_MAP_DATA_TYPE_BFLOAT16, 3, const_cast<void*>(ptr), dims, strides, box, es, CU_TENSOR_MAP_INTERLEAVE_NONE, sw,
      CU_TENSOR_MAP_L2_PROMOTION_L2_256B, CU_TENSOR_MAP_FLOAT_OOB_FILL_NONE);
}

}

extern "C" void kernel_launch(void* const* d_in, const int* in_sizes, int n_in, void* d_out, int out_size) {
  (void)in_sizes; (void)n_in; (void)out_size;
  PFN_encodeTiled enc = nullptr;
  cudaDriverEntryPointQueryResult qres;
  cudaGetDriverEntryPoint("cuTensorMapEncodeTiled", (void**)&enc, cudaEnableDefault, &qres);
  Params p;
  p.x = (const __nv_bfloat16*)d_in[0]; p.out = (__nv_bfloat16*)d_out;
  cudaGetSymbolAddress((void**)&p.xn, g_xn); cudaGetSymbolAddress((void**)&p.cnt, g_cnt);
  cudaGetSymbolAddress((void**)&p.abT, g_abT); cudaGetSymbolAddress((void**)&p.hT, g_hT);
  p.dr = (const __nv_bfloat16*)d_in[3]; p.di = (const __nv_bfloat16*)d_in[4];
  p.wg = (const __nv_bfloat16*)d_in[6]; p.wu = (const __nv_bfloat16*)d_in[7]; p.wd = (const __nv_bfloat16*)d_in[8];
  Maps maps;
  make_map(enc, &maps.xn, p.xn, S_, D_, 128, 64, CU_TENSOR_MAP_SWIZZLE_128B);
  make_map(enc, &maps.dr, d_in[3], D_, D_, 128, 64, CU_TENSOR_MAP_SWIZZLE_128B);
  make_map(enc, &maps.di, d_in[4], D_, D_, 128, 64, CU_TENSOR_MAP_SWIZZLE_128B);
  make_map(enc, &maps.wg, d_in[6], D_, F_, 64, 64, CU_TENSOR_MAP_SWIZZLE_128B);
  make_map(enc, &maps.wu, d_in[7], D_, F_, 64, 64, CU_TENSOR_MAP_SWIZZLE_128B);
  make_map(enc, &maps.cr, d_in[1], S_, S_, 128, 64, CU_TENSOR_MAP_SWIZZLE_128B);
  make_map(enc, &maps.ci, d_in[2], S_, S_, 128, 64, CU_TENSOR_MAP_SWIZZLE_128B);
  make_map3(enc, &maps.h, p.hT, F_, S_, 64, 64, 2, CU_TENSOR_MAP_SWIZZLE_128B);
  make_map(enc, &maps.ab, p.abT, 2 * D_, S_, 80, 64, CU_TENSOR_MAP_SWIZZLE_128B);
  make_map3(enc, &maps.wd, d_in[8], F_, D_, 32, 32, 5, CU_TENSOR_MAP_SWIZZLE_64B);
  cudaFuncSetAttribute(fused_kernel, cudaFuncAttributeMaxDynamicSharedMemorySize, SMEM_BYTES);
  cudaLaunchConfig_t cfg = {};
  cfg.gridDim = dim3(NUM_CTAS); cfg.blockDim = dim3(384); cfg.dynamicSmemBytes = SMEM_BYTES; cfg.stream = cudaStreamPerThread;
  cudaLaunchAttribute at[1];
  at[0].id = cudaLaunchAttributeClusterDimension; at[0].val.clusterDim.x = 2; at[0].val.clusterDim.y = 1; at[0].val.clusterDim.z = 1;
  cfg.attrs = at; cfg.numAttrs = 1;
  cudaLaunchKernelEx(&cfg, fused_kernel, p, maps);
}
```

```cpp
#include <cuda_runtime.h>
#include <cuda_bf16.h>
#include <cuda.h>
#include <stdint.h>

template<int TA, int TB, int SA> __device__ __forceinline__ void wgmma_ss_n128(float (&d)[64], uint64_t da, uint64_t db, int sd) {
  asm volatile("{\n.reg .pred p;\nsetp.ne.b32 p, %66, 0;\n"
    "wgmma.mma_async.sync.aligned.m64n128k16.f32.bf16.bf16 {%0, %1, %2, %3, %4, %5, %6, %7, %8, %9, %10, %11, %12, %13, %14, %15, %16, %17, %18, %19, %20, %21, %22, %23, %24, %25, %26, %27, %28, %29, %30, %31, %32, %33, %34, %35, %36, %37, %38, %39, %40, %41, %42, %43, %44, %45, %46, %47, %48, %49, %50, %51, %52, %53, %54, %55, %56, %57, %58, %59, %60, %61, %62, %63}, %64, %65, p, %69, 1, %67, %68;\n}\n"
    : "+f"(d[0]), "+f"(d[1]), "+f"(d[2]), "+f"(d[3]), "+f"(d[4]), "+f"(d[5]), "+f"(d[6]), "+f"(d[7]), "+f"(d[8]), "+f"(d[9]), "+f"(d[10]), "+f"(d[11]), "+f"(d[12]), "+f"(d[13]), "+f"(d[14]), "+f"(d[15]), "+f"(d[16]), "+f"(d[17]), "+f"(d[18]), "+f"(d[19]), "+f"(d[20]), "+f"(d[21]), "+f"(d[22]), "+f"(d[23]), "+f"(d[24]), "+f"(d[25]), "+f"(d[26]), "+f"(d[27]), "+f"(d[28]), "+f"(d[29]), "+f"(d[30]), "+f"(d[31]), "+f"(d[32]), "+f"(d[33]), "+f"(d[34]), "+f"(d[35]), "+f"(d[36]), "+f"(d[37]), "+f"(d[38]), "+f"(d[39]), "+f"(d[40]), "+f"(d[41]), "+f"(d[42]), "+f"(d[43]), "+f"(d[44]), "+f"(d[45]), "+f"(d[46]), "+f"(d[47]), "+f"(d[48]), "+f"(d[49]), "+f"(d[50]), "+f"(d[51]), "+f"(d[52]), "+f"(d[53]), "+f"(d[54]), "+f"(d[55]), "+f"(d[56]), "+f"(d[57]), "+f"(d[58]), "+f"(d[59]), "+f"(d[60]), "+f"(d[61]), "+f"(d[62]), "+f"(d[63])
    : "l"(da), "l"(db), "r"(sd), "n"(TA), "n"(TB), "n"(SA));
}
template<int TA, int TB, int SA> __device__ __forceinline__ void wgmma_ss_n160(float (&d)[80], uint64_t da, uint64_t db, int sd) {
  asm volatile("{\n.reg .pred p;\nsetp.ne.b32 p, %82, 0;\n"
    "wgmma.mma_async.sync.aligned.m64n160k16.f32.bf16.bf16 {%0, %1, %2, %3, %4, %5, %6, %7, %8, %9, %10, %11, %12, %13, %14, %15, %16, %17, %18, %19, %20, %21, %22, %23, %24, %25, %26, %27, %28, %29, %30, %31, %32, %33, %34, %35, %36, %37, %38, %39, %40, %41, %42, %43, %44, %45, %46, %47, %48, %49, %50, %51, %52, %53, %54, %55, %56, %57, %58, %59, %60, %61, %62, %63, %64, %65, %66, %67, %68, %69, %70, %71, %72, %73, %74, %75, %76, %77, %78, %79}, %80, %81, p, %85, 1, %83, %84;\n}\n"
    : "+f"(d[0]), "+f"(d[1]), "+f"(d[2]), "+f"(d[3]), "+f"(d[4]), "+f"(d[5]), "+f"(d[6]), "+f"(d[7]), "+f"(d[8]), "+f"(d[9]), "+f"(d[10]), "+f"(d[11]), "+f"(d[12]), "+f"(d[13]), "+f"(d[14]), "+f"(d[15]), "+f"(d[16]), "+f"(d[17]), "+f"(d[18]), "+f"(d[19]), "+f"(d[20]), "+f"(d[21]), "+f"(d[22]), "+f"(d[23]), "+f"(d[24]), "+f"(d[25]), "+f"(d[26]), "+f"(d[27]), "+f"(d[28]), "+f"(d[29]), "+f"(d[30]), "+f"(d[31]), "+f"(d[32]), "+f"(d[33]), "+f"(d[34]), "+f"(d[35]), "+f"(d[36]), "+f"(d[37]), "+f"(d[38]), "+f"(d[39]), "+f"(d[40]), "+f"(d[41]), "+f"(d[42]), "+f"(d[43]), "+f"(d[44]), "+f"(d[45]), "+f"(d[46]), "+f"(d[47]), "+f"(d[48]), "+f"(d[49]), "+f"(d[50]), "+f"(d[51]), "+f"(d[52]), "+f"(d[53]), "+f"(d[54]), "+f"(d[55]), "+f"(d[56]), "+f"(d[57]), "+f"(d[58]), "+f"(d[59]), "+f"(d[60]), "+f"(d[61]), "+f"(d[62]), "+f"(d[63]), "+f"(d[64]), "+f"(d[65]), "+f"(d[66]), "+f"(d[67]), "+f"(d[68]), "+f"(d[69]), "+f"(d[70]), "+f"(d[71]), "+f"(d[72]), "+f"(d[73]), "+f"(d[74]), "+f"(d[75]), "+f"(d[76]), "+f"(d[77]), "+f"(d[78]), "+f"(d[79])
    : "l"(da), "l"(db), "r"(sd), "n"(TA), "n"(TB), "n"(SA));
}

namespace {

constexpr int S_ = 2048, D_ = 640, F_ = 1728;
constexpr int A_CHUNK   = 16384;
constexpr int RING1_OFF = 10 * A_CHUNK;
constexpr int R1        = 4;
constexpr int SLOT2     = 36864;
constexpr int R2        = 6;
constexpr int BAR_OFF   = RING1_OFF + R1 * 16384;
constexpr int TL_OFF    = BAR_OFF + 512;
constexpr int SMEM_BYTES = TL_OFF + 512;
constexpr int NUM_CTAS  = 132;
#define NC1 38
#define ND1 13
#define MAPV 1
#define REL1 0
#define REL2 0
#define FREE0 3
#define ZERO_NS 5000
#define PFKB 7
#define STAG 6
#define EARLYWG kh
#define XAHEAD 2
#define XW 1
#define PFW 9
#define KHA 1
#define PF 0

__device__ __nv_bfloat16 g_xn[S_ * D_];
__device__ __nv_bfloat16 g_abT[2 * D_ * S_];
__device__ __nv_bfloat16 g_hT[F_ * S_];
constexpr int CNT_XN = 0, CNT_H = 16, CNT_HX = 32, CNT_A = 48, CNT_B = 49, CNT_DONE = 50, CNT_TOTAL = 51;
__device__ unsigned g_cnt[CNT_TOTAL * 32];
#define TL(idx) do {} while (0)

struct Params {
  const __nv_bfloat16* x; __nv_bfloat16* out;
  __nv_bfloat16* xn; unsigned* cnt; __nv_bfloat16* abT; __nv_bfloat16* hT;
  const __nv_bfloat16 *dr, *di, *wg, *wu, *wd;
};
struct Maps {
  CUtensorMap xn, dr, di, wg, wu, cr, ci, h, ab, wd;
};

__device__ __forceinline__ uint32_t smem_u32(const void* p) { return (uint32_t)__cvta_generic_to_shared(p); }
__device__ __forceinline__ void mbar_init(uint32_t bar, uint32_t count) { asm volatile("mbarrier.init.shared::cta.b64 [%0], %1;" :: "r"(bar), "r"(count)); }
__device__ __forceinline__ void mbar_expect_tx(uint32_t bar, uint32_t bytes) { asm volatile("mbarrier.arrive.expect_tx.shared::cta.b64 _, [%0], %1;" :: "r"(bar), "r"(bytes) : "memory"); }
__device__ __forceinline__ void mbar_arrive(uint32_t bar) { asm volatile("mbarrier.arrive.shared::cta.b64 _, [%0];" :: "r"(bar) : "memory"); }
__device__ __forceinline__ void mbar_arrive_cta(uint32_t bar, uint32_t cta) {
  asm volatile("{\n.reg .b32 ra;\nmapa.shared::cluster.u32 ra, %0, %1;\nmbarrier.arrive.shared::cluster.b64 _, [ra];\n}\n" :: "r"(bar), "r"(cta) : "memory");
}
__device__ __forceinline__ void mbar_wait(uint32_t bar, uint32_t parity) {
  asm volatile("{\n.reg .pred p;\n.reg .u32 n;\nmov.u32 n, 0;\n"
    "LAB_WAIT:\n"
    "mbarrier.try_wait.parity.shared::cta.b64 p, [%0], %1;\n"
    "@p bra LAB_DONE;\n"
    "add.u32 n, n, 1;\n"
    "setp.lt.u32 p, n, 4000000;\n"
    "@p bra LAB_WAIT;\n"
    "trap;\n"
    "LAB_DONE:\n}\n" :: "r"(bar), "r"(parity) : "memory");
}
__device__ __forceinline__ void tma_load(uint32_t dst, const CUtensorMap* map, int c0, int c1, uint32_t bar) {
  asm volatile("cp.async.bulk.tensor.2d.shared::cluster.global.mbarrier::complete_tx::bytes [%0], [%1, {%3, %4}], [%2];"
    :: "r"(dst), "l"(map), "r"(bar), "r"(c0), "r"(c1) : "memory");
}
__device__ __forceinline__ void tma_load_mc(uint32_t dst, const CUtensorMap* map, int c0, int c1, uint32_t bar) {
  asm volatile("cp.async.bulk.tensor.2d.shared::cluster.global.mbarrier::complete_tx::bytes.multicast::cluster [%0], [%1, {%3, %4}], [%2], %5;"
    :: "r"(dst), "l"(map), "r"(bar), "r"(c0), "r"(c1), "h"((uint16_t)3) : "memory");
}
__device__ __forceinline__ void tma_load_3d(uint32_t dst, const CUtensorMap* map, int c1, int c2, uint32_t bar) {
  asm volatile("cp.async.bulk.tensor.3d.shared::cluster.global.mbarrier::complete_tx::bytes [%0], [%1, {%5, %3, %4}], [%2];"
    :: "r"(dst), "l"(map), "r"(bar), "r"(c1), "r"(c2), "r"(0) : "memory");
}
__device__ __forceinline__ void tma_load_3d_mc(uint32_t dst, const CUtensorMap* map, int c1, int c2, uint32_t bar) {
  asm volatile("cp.async.bulk.tensor.3d.shared::cluster.global.mbarrier::complete_tx::bytes.multicast::cluster [%0], [%1, {%5, %3, %4}], [%2], %6;"
    :: "r"(dst), "l"(map), "r"(bar), "r"(c1), "r"(c2), "r"(0), "h"((uint16_t)3) : "memory");
}
__device__ __forceinline__ void tma_prefetch(const CUtensorMap* map, int c0, int c1) {
  asm volatile("cp.async.bulk.prefetch.tensor.2d.L2.global [%0, {%1, %2}];" :: "l"(map), "r"(c0), "r"(c1) : "memory");
}
__device__ __forceinline__ void prefetch_map(const CUtensorMap* map) { asm volatile("prefetch.tensormap [%0];" :: "l"(map) : "memory"); }
__device__ __forceinline__ void l2_prefetch(const void* p, uint32_t bytes) { asm volatile("cp.async.bulk.prefetch.L2.global [%0], %1;" :: "l"(p), "r"(bytes) : "memory"); }
__device__ __forceinline__ void wgmma_fence() { asm volatile("wgmma.fence.sync.aligned;" ::: "memory"); }
__device__ __forceinline__ void wgmma_commit() { asm volatile("wgmma.commit_group.sync.aligned;" ::: "memory"); }
template<int N> __device__ __forceinline__ void wgmma_wait() { asm volatile("wgmma.wait_group.sync.aligned %0;" :: "n"(N) : "memory"); }
template<int N> __device__ __forceinline__ void fence_acc(float (&d)[N]) {
  #pragma unroll
  for (int i = 0; i < N; i++) asm volatile("" : "+f"(d[i]) :: "memory");
}
__device__ __forceinline__ void named_sync(int id, int n) { asm volatile("bar.sync %0, %1;" :: "r"(id), "r"(n) : "memory"); }
__device__ __forceinline__ void named_arrive(int id, int n) { asm volatile("bar.arrive %0, %1;" :: "r"(id), "r"(n) : "memory"); }
template<int R> __device__ __forceinline__ void reg_alloc() { asm volatile("setmaxnreg.inc.sync.aligned.u32 %0;" :: "n"(R)); }
template<int R> __device__ __forceinline__ void reg_dealloc() { asm volatile("setmaxnreg.dec.sync.aligned.u32 %0;" :: "n"(R)); }
__device__ __forceinline__ void fence_proxy_async_global() { asm volatile("fence.proxy.async.global;" ::: "memory"); }
__device__ __forceinline__ void red_release(unsigned* p) { asm volatile("red.release.gpu.global.add.u32 [%0], 1;" :: "l"(p) : "memory"); }
template<int SLEEP_NS>
__device__ __forceinline__ void wait_counter(const unsigned* p, unsigned target) {
  asm volatile("{\n.reg .pred p;\n.reg .u32 n, v;\nmov.u32 n, 0;\n"
    "LAB_WAIT:\n"
    "ld.acquire.gpu.global.u32 v, [%0];\n"
    "setp.ge.u32 p, v, %1;\n"
    "@p bra LAB_DONE;\n"
    "nanosleep.u32 %2;\n"
    "add.u32 n, n, 1;\n"
    "setp.lt.u32 p, n, 2000000;\n"
    "@p bra LAB_WAIT;\n"
    "trap;\n"
    "LAB_DONE:\n}\n" :: "l"(p), "r"(target), "n"(SLEEP_NS) : "memory");
}
constexpr uint32_t HI_SW128 = (1024 >> 4) | (1u << 30);
constexpr uint32_t HI_SW64  = (512 >> 4) | (2u << 30);
constexpr uint32_t DBASE    = 0x400 >> 4;
constexpr uint32_t LBO_NONE = 1u << 16;
constexpr uint32_t LBO_2K   = (2048u >> 4) << 16;
__device__ __forceinline__ uint64_t mk_desc(uint32_t lo, uint32_t hi) { uint64_t d; asm("mov.b64 %0, {%1, %2};" : "=l"(d) : "r"(lo), "r"(hi)); return d; }

__device__ __forceinline__ uint32_t pack_bf16(float lo, float hi) {
  uint32_t r; asm("cvt.rn.bf16x2.f32 %0, %1, %2;" : "=r"(r) : "f"(hi), "f"(lo)); return r;
}
__device__ __forceinline__ float bf_lo(uint32_t v) { return __uint_as_float(v << 16); }
__device__ __forceinline__ float bf_hi(uint32_t v) { return __uint_as_float(v & 0xffff0000u); }
__device__ __forceinline__ float round_bf(float v) { return bf_lo(pack_bf16(v, 0.f)); }
__device__ __forceinline__ uint32_t norm2(uint32_t x, uint32_t m2, uint32_t ih2, uint32_t il2) {
  uint32_t d, t, r;
  asm("sub.rn.bf16x2 %0, %1, %2;" : "=r"(d) : "r"(x), "r"(m2));
  asm("mul.rn.bf16x2 %0, %1, %2;" : "=r"(t) : "r"(d), "r"(il2));
  asm("fma.rn.bf16x2 %0, %1, %2, %3;" : "=r"(r) : "r"(d), "r"(ih2), "r"(t));
  return r;
}
__device__ __forceinline__ float silu_mul(float g, float u) {
  float e, r;
  asm("ex2.approx.ftz.f32 %0, %1;" : "=f"(e) : "f"(g * -1.4426950408889634f));
  asm("rcp.approx.ftz.f32 %0, %1;" : "=f"(r) : "f"(e + 1.0f));
  return (g * u) * r;
}
__device__ __forceinline__ int xn_row(int t) { return (t & ~30) | ((t & 6) << 2) | ((t & 24) >> 2); }
__device__ __forceinline__ int unit_of(int role, int t) {
  const int two_ab = (role & 5) == 0;
  if (t == 0) return role;
  if (t == 1 && two_ab) return 8 + (role >> 1);
  return 9 + 3 * role + (role > 4) + (role > 6) + t - two_ab;
}

__device__ __forceinline__ void prefetch_unit(const Maps& maps, int unit, int kb) {
  if (unit < 10) tma_prefetch(unit < 5 ? &maps.dr : &maps.di, kb * 64, (unit < 5 ? unit : unit - 5) * 128);
  else { tma_prefetch(&maps.wg, (unit - 10) * 64, kb * 64); tma_prefetch(&maps.wu, (unit - 10) * 64, kb * 64); }
}

struct Ctx {
  uint32_t sbase, full1, empty1, full2, empty2, flagb, pub, xfull;
  int wg, warp, lane, zero;
  bool elect;
};

template<int MODE, bool LAST>
__device__ __forceinline__ void stage1_mma(const Ctx& c, float (&acc)[2][64], int it0, bool first, bool has_next, bool free_all) {
  int prev = 0;
  #pragma unroll 1
  for (int kb = 0; kb < 10; kb++) {
    const int it = it0 + kb;
    const int slot = it & 3;
    const uint32_t bx = DBASE + kb * (A_CHUNK >> 4) + LBO_NONE;
    const uint32_t ar = DBASE + slot * 1024 + ((RING1_OFF >> 4) + LBO_NONE);
    if (MODE != 2 && first) mbar_wait(c.xfull + 8 * kb, 0);
    mbar_wait(c.full1 + 8 * slot, (it >> 2) & 1);
    if (kb == 9 && has_next) named_arrive(1 + (c.wg ^ 1), 256);
    wgmma_fence();
    #pragma unroll
    for (int k = 0; k < 4; k++) {
      #pragma unroll
      for (int i = 0; i < 2; i++) {
        if (MODE == 2) wgmma_ss_n128<1, 0, 1>(acc[i], mk_desc(ar + i * 512 + k * 128, HI_SW128), mk_desc(bx + k * 2, HI_SW128), (kb | k) != 0);
        else           wgmma_ss_n128<0, 0, (MODE == 1 ? -1 : 1)>(acc[i], mk_desc(ar + i * 512 + k * 2, HI_SW128), mk_desc(bx + k * 2, HI_SW128), (kb | k) != 0);
      }
      if (k == REL1) {
        wgmma_commit();
        wgmma_wait<1>();
        if (kb > 0 && c.elect) {
          mbar_arrive(c.empty1 + 8 * prev);
          if (LAST && kb >= FREE0) {
            const int j = kb - FREE0;
            if (FREE0 == 3 ? (kb & 1) : true) {
              const uint32_t b = c.empty2 + 8 * (FREE0 == 3 ? (j >> 1) : j);
              mbar_arrive_cta(b, 0); mbar_arrive_cta(b, 1);
            }
          }
        }
        if (k < 3) wgmma_fence();
      }
    }
    if (REL1 < 3) wgmma_commit();
    prev = slot;
  }
  #pragma unroll 1
  for (int z = c.zero; z < 1; z++) {
    wgmma_wait<0>();
    if (c.elect) {
      mbar_arrive(c.empty1 + 8 * prev);
      TL(33 + (it0 / 10) * 4);
      if (LAST || free_all) {
        #pragma unroll
        for (int j = LAST ? 4 : 0; j < R2; j++) { mbar_arrive_cta(c.empty2 + 8 * j, 0); mbar_arrive_cta(c.empty2 + 8 * j, 1); }
      }
    }
  }
  wgmma_wait<0>();
  fence_acc(acc[0]); fence_acc(acc[1]);
}
__device__ __forceinline__ void store_ab(const float (&acc)[2][64], uint4* dst) {
  #pragma unroll
  for (int i = 0; i < 2; i++)
    #pragma unroll
    for (int hf = 0; hf < 2; hf++)
      #pragma unroll
      for (int J = 0; J < 4; J++) {
        const int r = 16 * J + 2 * hf;
        dst[(i * 64 + hf * 8) * (S_ / 8) + J * 4] = make_uint4(pack_bf16(acc[i][r], acc[i][r + 1]), pack_bf16(acc[i][r + 4], acc[i][r + 5]),
                                                               pack_bf16(acc[i][r + 8], acc[i][r + 9]), pack_bf16(acc[i][r + 12], acc[i][r + 13]));
      }
}
__device__ __forceinline__ void store_h_slice(const float (&acc)[2][64], uint4* dst, int sl) {
  const int hf = sl >> 2, J = sl & 3;
  uint32_t w[4];
  #pragma unroll
  for (int b = 0; b < 4; b++) {
    const int r = 16 * J + 4 * b + 2 * hf;
    w[b] = pack_bf16(silu_mul(acc[0][r], acc[1][r]), silu_mul(acc[0][r + 1], acc[1][r + 1]));
  }
  dst[hf * 8 * (S_ / 8) + J * 4] = make_uint4(w[0], w[1], w[2], w[3]);
}
__device__ __forceinline__ void publish(const Ctx& c, int t) {
  if (c.elect) TL(34 + t * 4);
  __syncwarp();
  if (c.lane == 0) mbar_arrive(c.pub + 8 * t);
}
__device__ __forceinline__ void release2(const Ctx& c, int slot) {
  if (c.elect) { mbar_arrive_cta(c.empty2 + 8 * slot, 0); mbar_arrive_cta(c.empty2 + 8 * slot, 1); }
}
template<bool DPART>
__device__ __forceinline__ void stage2_kb(const Ctx& c, float (&acc)[80], int slot, int ph, int prev, bool rel) {
  const uint32_t sa = DBASE + slot * (SLOT2 >> 4) + c.wg * 512 + LBO_NONE, sb = DBASE + slot * (SLOT2 >> 4) + (1024 + (DPART ? LBO_2K : LBO_NONE));
  mbar_wait(c.full2 + 8 * slot, ph);
  wgmma_fence();
  #pragma unroll
  for (int k = 0; k < 4; k++) {
    if (DPART) wgmma_ss_n160<1, 1, 1>(acc, mk_desc(sa + k * 128, HI_SW128), mk_desc(sb + (k >> 1) * 640 + (k & 1) * 64, HI_SW64), 1);
    else       wgmma_ss_n160<0, 0, 1>(acc, mk_desc(sa + k * 2, HI_SW128), mk_desc(sb + k * 2, HI_SW128), 1);
    if (k == REL2) {
      wgmma_commit();
      wgmma_wait<1>();
      if (rel) release2(c, prev);
      if (k < 3) wgmma_fence();
    }
  }
  if (REL2 < 3) wgmma_commit();
}

template<int KH>
__device__ __forceinline__ void stage2_finish(const Ctx& c, float (&acc)[80], const uint32_t (&xr)[2][10], __nv_bfloat16* outw) {
  #pragma unroll
  for (int j = 0; j < 10; j++) {
    acc[KH * 40 + 4 * j] += bf_lo(xr[0][j]); acc[KH * 40 + 4 * j + 1] += bf_hi(xr[0][j]);
    acc[KH * 40 + 4 * j + 2] += bf_lo(xr[1][j]); acc[KH * 40 + 4 * j + 3] += bf_hi(xr[1][j]);
  }
  const uint32_t stg = c.sbase + c.warp * SLOT2 + c.wg * 8192;
  const uint32_t sw = stg + (c.lane & 15) * 336 + (c.lane >> 4) * 16;
  #pragma unroll
  for (int jj = 0; jj < 10; jj++) {
    asm volatile("stmatrix.sync.aligned.m8n8.x4.shared.b16 [%0], {%1, %2, %3, %4};" :: "r"(sw + jj * 32),
                 "r"(pack_bf16(acc[8 * jj], acc[8 * jj + 1])), "r"(pack_bf16(acc[8 * jj + 2], acc[8 * jj + 3])),
                 "r"(pack_bf16(acc[8 * jj + 4], acc[8 * jj + 5])), "r"(pack_bf16(acc[8 * jj + 6], acc[8 * jj + 7])) : "memory");
  }
  __syncwarp();
  uint4 v[10];
  #pragma unroll
  for (int i = 0; i < 10; i++) {
    const int idx = i * 32 + c.lane, row = idx / 20, ch = idx - row * 20;
    asm volatile("ld.shared.v4.u32 {%0, %1, %2, %3}, [%4];" : "=r"(v[i].x), "=r"(v[i].y), "=r"(v[i].z), "=r"(v[i].w) : "r"(stg + row * 336 + ch * 16) : "memory");
  }
  #pragma unroll
  for (int i = 0; i < 10; i++) {
    const int idx = i * 32 + c.lane, row = idx / 20, ch = idx - row * 20;
    asm volatile("red.global.add.noftz.v4.bf16x2 [%0], {%1, %2, %3, %4};" :: "l"(outw + row * D_ + ch * 8), "r"(v[i].x), "r"(v[i].y), "r"(v[i].z), "r"(v[i].w) : "memory");
  }
}

__global__ void __launch_bounds__(384, 1)
fused_kernel(const __grid_constant__ Params p, const __grid_constant__ Maps maps) {
  extern __shared__ __align__(1024) uint8_t smem_raw[];
  const int cl = blockIdx.x >> 1, rank = blockIdx.x & 1;
  const bool extra = cl >= 64;
  const int tok = (blockIdx.x & 127) * 16 + ((threadIdx.x >> 4) & 15), l16 = threadIdx.x & 15;
  uint4 v[5];
  uint32_t x0 = 0;
  if (threadIdx.x < 256) {
    const uint4* xs = reinterpret_cast<const uint4*>(p.x + (size_t)tok * D_);
    #pragma unroll
    for (int i = 0; i < 5; i++) v[i] = __ldg(xs + l16 + 16 * i);
    x0 = __ldg(reinterpret_cast<const uint32_t*>(xs));
  }
  int kh, nt, grp;
  {
    int pos, half;
    if (cl >= 4 && cl < 36) { half = 0; pos = (cl - 4) & 7; nt = (cl - 4) >> 3; }
    else if (cl >= 36)      { half = 1; nt = (cl - 36) / 7; pos = 1 + (cl - 36) - nt * 7; nt &= 3; }
    else                    { half = 1; pos = 0; nt = cl; }
    kh = (pos >> 2) ^ KHA ^ 1; grp = (pos & 3) * 2 + half;
  }
  const int mb2 = grp * 2 + rank;
  const int role = kh + 2 * ((nt & 1) * 2 + rank);
  const int mb1 = extra ? (cl - 64) * 8 + rank : grp * 2 + (nt >> 1);

  Ctx c;
  c.sbase = __shfl_sync(0xffffffffu, smem_u32(smem_raw), 0);
  c.zero = __shfl_sync(0xffffffffu, threadIdx.x >> 10, 0);
  c.full1 = c.sbase + BAR_OFF; c.empty1 = c.full1 + 8 * R1; c.full2 = c.empty1 + 8 * R1; c.empty2 = c.full2 + 8 * R2;
  c.flagb = c.empty2 + 8 * R2; c.pub = c.flagb + 8 * 4; c.xfull = c.pub + 8 * 5;
  c.wg = __shfl_sync(0xffffffffu, threadIdx.x >> 7, 0);
  c.warp = __shfl_sync(0xffffffffu, (threadIdx.x >> 5) & 3, 0);
  c.lane = threadIdx.x & 31;
  c.elect = (threadIdx.x & 127) == 0;

  const int nT = extra ? 4 : 5 - kh;
  const int nC = kh ? NC1 : 64 - NC1, c0 = kh ? 0 : NC1, nD = kh ? ND1 : 27 - ND1, d0 = kh ? 0 : ND1;
  const int n2 = nC + nD;

  if (c.wg == 2) {
    reg_dealloc<40>();
    int wlo = c.warp & 1, whi = c.warp >> 1;
    asm volatile("" : "+r"(wlo)); asm volatile("" : "+r"(whi));
    const bool w0 = !whi && !wlo, w1 = !whi && wlo, w2 = whi && !wlo;
    if (c.lane == 0) {
      if (w0) {
        #pragma unroll
        for (int i = 0; i < 2 * R1; i++) mbar_init(c.full1 + 8 * i, 1);
      } else if (w1) {
        prefetch_map(&maps.xn);
        #pragma unroll
        for (int i = 0; i < 10; i++) mbar_init(c.xfull + 8 * i, 1);
      } else if (w2) {
        #pragma unroll
        for (int i = 0; i < R2; i++) { mbar_init(c.full2 + 8 * i, 1); mbar_init(c.empty2 + 8 * i, 4); }
      } else {
        #pragma unroll
        for (int i = 0; i < 4; i++) mbar_init(c.flagb + 8 * i, 1);
        #pragma unroll
        for (int i = 0; i < 5; i++) mbar_init(c.pub + 8 * i, 4);
        if ((c.sbase & 0x3FFFFu) != 0x400u) asm volatile("trap;");
      }
      asm volatile("fence.mbarrier_init.release.cluster;" ::: "memory");
      if (w0) TL(11);
    }
    __syncwarp();
    asm volatile("barrier.cluster.arrive.relaxed.aligned;" ::: "memory");
    asm volatile("barrier.cluster.wait.acquire.aligned;" ::: "memory");
    if (w0) {
      if (c.lane == 0) {
        int it = 0;
        for (int t = 0; t < nT; t++) {
          const int unit = extra ? 36 : unit_of(role, t);
          for (int kb = 0; kb < 10; kb++, it++) {
            const int slot = it & 3;
            const uint32_t full = c.full1 + 8 * slot;
            const uint32_t dst = c.sbase + RING1_OFF + slot * 16384;
            mbar_wait(c.empty1 + 8 * slot, ((it >> 2) & 1) ^ 1);
            mbar_expect_tx(full, extra ? 32768 : 16384);
            if (unit < 10) {
              tma_load(dst, unit < 5 ? &maps.dr : &maps.di, kb * 64, (unit < 5 ? unit : unit - 5) * 128, full);
            } else {
              tma_load(dst, &maps.wg, (unit - 10) * 64, kb * 64, full);
              tma_load(dst + 8192, &maps.wu, (unit - 10) * 64, kb * 64, full);
            }
            if (it == 3) { TL(12); prefetch_map(&maps.wg); prefetch_map(&maps.wu); prefetch_map(&maps.di); }
            if (kb == PFKB && t + 2 < nT && !extra && mb1 < 10) prefetch_unit(maps, unit_of(role, t + 2), mb1);
            if (extra) {
              if (kb == 0) { wait_counter<100>(&p.cnt[(CNT_XN + mb1 + 2 * t) * 32], 8); fence_proxy_async_global(); }
              tma_load(c.sbase + kb * A_CHUNK, &maps.xn, kb * 64, (mb1 + 2 * t) * 128, full);
            }
          }
        }
      }
    } else if (w1) {
      if (c.lane == 0 && !extra) {
        #pragma unroll
        for (int i = 0; i < 10; i++) mbar_expect_tx(c.xfull + 8 * i, A_CHUNK);
        wait_counter<0>(&p.cnt[(CNT_XN + mb1) * 32], 8);
        fence_proxy_async_global();
        TL(1);
        #pragma unroll
        for (int i = 0; i < 5; i++) {
          if (i >= XAHEAD) mbar_wait(c.xfull + 8 * (2 * (i - XAHEAD) + XW), 0);
          tma_load_mc(c.sbase + (2 * i + rank) * A_CHUNK, &maps.xn, (2 * i + rank) * 64, mb1 * 128, c.xfull + 8 * (2 * i + rank));
        }
        if (PFW >= 0) mbar_wait(c.xfull + 8 * PFW, 0);
        TL(14);
        if (mb1 < 10) prefetch_unit(maps, unit_of(role, 1), mb1);
        prefetch_map(&maps.cr); prefetch_map(&maps.ci); prefetch_map(&maps.ab); prefetch_map(&maps.h); prefetch_map(&maps.wd);
        int slot = 0, ph = 0;
        for (int i = 0; i < n2; i++) {
          if (PF > 0 && ((i + PF) & 3) == nt && i + PF < nC) { const int kc = c0 + i + PF; tma_prefetch(kc >= 32 ? &maps.ci : &maps.cr, (kc & 31) * 64, mb2 * 128); }
          const uint32_t full = c.full2 + 8 * slot;
          const uint32_t dst = c.sbase + slot * SLOT2;
          mbar_wait(c.empty2 + 8 * slot, ph);
          if (i == 0) { TL(2); mbar_wait(c.flagb, 0); fence_proxy_async_global(); TL(3); }
          if (c0 + i == max(c0, 32)) { mbar_wait(c.flagb + 24, 0); fence_proxy_async_global(); }
          mbar_expect_tx(full, SLOT2);
          if (i < nC) {
            const int kc = c0 + i;
            const int im = kc >= 32;
            const int kk = (kc & 31) * 64;
            tma_load(dst, im ? &maps.ci : &maps.cr, kk, mb2 * 128, full);
            tma_load_mc(dst + 16384 + rank * 10240, &maps.ab, kk, im * 640 + nt * 160 + rank * 80, full);
          } else {
            const int kd = d0 + i - nC;
            tma_load_3d_mc(dst + 16384 + rank * 10240, &maps.wd, kd * 64 + rank * 32, nt * 5, full);
            if (i == nC) { TL(4); mbar_wait(c.flagb + 8, 0); fence_proxy_async_global(); TL(5); }
            if (kd == 26) { mbar_wait(c.flagb + 16, 0); fence_proxy_async_global(); }
            tma_load_3d(dst, &maps.h, kd * 64, mb2 * 2, full);
          }
          if (++slot == R2) { slot = 0; ph ^= 1; }
        }
      }
    } else if (w2) {
      const uint32_t total = D_ * F_ * 2, per = ((total + NUM_CTAS - 1) / NUM_CTAS + 127) & ~127u, beg = blockIdx.x * per;
      if (c.lane == 0 && !extra && mb1 < 6) prefetch_unit(maps, role, 4 + mb1);
      __nanosleep(ZERO_NS);
      if (!extra) {
        __nv_bfloat16* zb = p.out + (size_t)mb2 * 128 * D_ + nt * 160 + kh * 80;
        #pragma unroll 4
        for (int i = c.lane; i < 1280; i += 32) { const int r = i / 10; *reinterpret_cast<uint4*>(zb + r * D_ + (i - r * 10) * 8) = make_uint4(0u, 0u, 0u, 0u); }
      }
      __syncwarp();
      if (c.lane == 1) {
        __nanosleep(6000);
        if (beg < total) l2_prefetch((const char*)p.wd + beg, min(per, total - beg));
      } else if (c.lane == 0) {
        for (int t = 0; t < nT; t++) {
          mbar_wait(c.pub + 8 * t, 0);
          const int unit = unit_of(role, t);
          red_release(&p.cnt[(extra ? CNT_HX + mb1 + 2 * t : unit < 5 ? CNT_A : unit < 10 ? CNT_B : CNT_H + mb1) * 32]);
          TL(35 + t * 4);
        }
      }
    } else {
      if (!extra) {
        named_sync(3, 256 + 32);
        if (c.lane == 0) {
          red_release(&p.cnt[(CNT_XN + (blockIdx.x >> 3)) * 32]);
          TL(55);
          __nanosleep(5000);
          wait_counter<300>(&p.cnt[CNT_A * 32], 80);           fence_proxy_async_global(); mbar_arrive(c.flagb);
          wait_counter<300>(&p.cnt[CNT_B * 32], 80);           fence_proxy_async_global(); mbar_arrive(c.flagb + 24);
          wait_counter<500>(&p.cnt[(CNT_H + mb2) * 32], 26);   fence_proxy_async_global(); mbar_arrive(c.flagb + 8);
          wait_counter<500>(&p.cnt[(CNT_HX + mb2) * 32], 1);   fence_proxy_async_global(); mbar_arrive(c.flagb + 16);
          if (atomicAdd(&p.cnt[CNT_DONE * 32], 1u) == 127u) {
            for (int i = 0; i < CNT_TOTAL; i++) p.cnt[i * 32] = 0;
          }
        }
      }
    }
  } else {
    asm volatile("barrier.cluster.arrive.relaxed.aligned;" ::: "memory");
    if (!extra) {
      const float sh = bf_lo(x0);
      float s0 = 0.f, s1 = 0.f, q0 = 0.f, q1 = 0.f;
      #pragma unroll
      for (int i = 0; i < 5; i++) {
        const uint32_t w[4] = {v[i].x, v[i].y, v[i].z, v[i].w};
        #pragma unroll
        for (int j = 0; j < 4; j++) { const float a = bf_lo(w[j]) - sh, b = bf_hi(w[j]) - sh; s0 += a; s1 += b; q0 = fmaf(a, a, q0); q1 = fmaf(b, b, q1); }
      }
      float s = s0 + s1, ss = q0 + q1;
      #pragma unroll
      for (int o = 1; o < 16; o <<= 1) { s += __shfl_xor_sync(0xffffffffu, s, o); ss += __shfl_xor_sync(0xffffffffu, ss, o); }
      const float dm = s * (1.0f / D_);
      const float var = fmaxf(fmaf(-dm, dm, ss * (1.0f / D_)), 0.f);
      float sd, inv;
      asm("sqrt.approx.f32 %0, %1;" : "=f"(sd) : "f"(round_bf(round_bf(var) + 1e-5f)));
      asm("rcp.approx.f32 %0, %1;" : "=f"(inv) : "f"(round_bf(sd)));
      const float ih = round_bf(inv);
      const uint32_t m2 = pack_bf16(sh + dm, sh + dm), ih2 = pack_bf16(ih, ih), il2 = pack_bf16(inv - ih, inv - ih);
      uint4* dst = reinterpret_cast<uint4*>(p.xn + (size_t)xn_row(tok) * D_);
      #pragma unroll
      for (int i = 0; i < 5; i++)
        dst[l16 + 16 * i] = make_uint4(norm2(v[i].x, m2, ih2, il2), norm2(v[i].y, m2, ih2, il2), norm2(v[i].z, m2, ih2, il2), norm2(v[i].w, m2, ih2, il2));
      named_arrive(3, 256 + 32);
    }
    reg_alloc<232>();
    asm volatile("barrier.cluster.wait.acquire.aligned;" ::: "memory");
    if (threadIdx.x == 0) TL(54);

    const int rl = c.warp * 16 + (c.lane >> 2);
    const int nT1 = extra ? nT : nT - 1;
    #pragma unroll 1
    for (int t = c.wg; t < nT1; t += 2) {
      const int unit = extra ? 36 : unit_of(role, t);
      const int col = (extra ? mb1 + 2 * t : mb1) * 128 + (c.lane & 3) * 8;
      if (t > 0) named_sync(1 + c.wg, 256);
      const bool free_all = !extra && t == nT - 2;
      const bool has_next = t < nT - 1;
      float acc[2][64];
      if (unit < 10) {
        if (unit < 5) stage1_mma<0, false>(c, acc, t * 10, t == 0, has_next, free_all);
        else          stage1_mma<1, false>(c, acc, t * 10, t == 0, has_next, free_all);
        store_ab(acc, reinterpret_cast<uint4*>(p.abT + (size_t)(unit * 128 + rl) * S_ + col));
      } else {
        stage1_mma<2, false>(c, acc, t * 10, false, has_next, free_all);
        uint4* dst = reinterpret_cast<uint4*>(p.hT + (size_t)((unit - 10) * 64 + rl) * S_ + col);
        #pragma unroll
        for (int sl = 0; sl < 8; sl++) store_h_slice(acc, dst, sl);
      }
      publish(c, t);
    }

    if (!extra) {
      const size_t obase = (size_t)(mb2 * 128 + c.wg * 64 + rl) * D_ + nt * 160 + kh * 80 + (c.lane & 3) * 2;
      uint32_t xr[2][10];
      __nv_bfloat16* outw = p.out + (size_t)(mb2 * 128 + c.wg * 64 + c.warp * 16) * D_ + nt * 160;
      float acc[80];
      int i0 = 0;
      if (((nT - 1) & 1) == c.wg) {
        const int t = nT - 1;
        named_sync(1 + c.wg, 256);
        uint32_t gu[2][32];
        {
          float acc1[2][64];
          stage1_mma<2, true>(c, acc1, t * 10, false, true, false);
          #pragma unroll
          for (int r = 0; r < 32; r++) { gu[0][r] = pack_bf16(acc1[0][2 * r], acc1[0][2 * r + 1]); gu[1][r] = pack_bf16(acc1[1][2 * r], acc1[1][2 * r + 1]); }
        }
        #pragma unroll
        for (int r = 0; r < 80; r++) acc[r] = 0.f;
        uint4* dst = reinterpret_cast<uint4*>(p.hT + (size_t)((unit_of(role, t) - 10) * 64 + rl) * S_ + mb1 * 128 + (c.lane & 3) * 8);
        if (c.elect) TL(20 + c.wg);
        #pragma unroll
        for (int i = 0; i < 8; i++) {
          stage2_kb<false>(c, acc, i % R2, i / R2, (i + R2 - 1) % R2, i > 0);
          uint32_t w[4];
          #pragma unroll
          for (int b = 0; b < 4; b++) {
            const int r = 8 * (i & 3) + 2 * b + (i >> 2);
            w[b] = pack_bf16(silu_mul(bf_lo(gu[0][r]), bf_lo(gu[1][r])), silu_mul(bf_hi(gu[0][r]), bf_hi(gu[1][r])));
          }
          dst[(i >> 2) * 8 * (S_ / 8) + (i & 3) * 4] = make_uint4(w[0], w[1], w[2], w[3]);
        }
        publish(c, t);
        wgmma_wait<0>();
        fence_acc(acc);
        i0 = 8;
      }
      #pragma unroll
      for (int hf = 0; hf < 2; hf++)
        #pragma unroll
        for (int j = 0; j < 10; j++) xr[hf][j] = __ldg(reinterpret_cast<const uint32_t*>(p.x + obase + hf * 8 * D_ + j * 8));
      if (i0 == 0) {
        #pragma unroll
        for (int r = 0; r < 80; r++) acc[r] = 0.f;
        named_sync(1 + c.wg, 256);
        if (c.elect) TL(20 + c.wg);
      }
      int slot = i0 % R2, ph = i0 / R2, prev = (i0 + R2 - 1) % R2;
      #pragma unroll 1
      for (int i = i0; i < nC; i++) {
        stage2_kb<false>(c, acc, slot, ph, prev, i > 0);
        prev = slot;
        if (++slot == R2) { slot = 0; ph ^= 1; }
      }
      if (c.elect) TL(22 + c.wg);
      #pragma unroll 1
      for (int i = nC; i < n2; i++) {
        if (STAG > 0 && i == n2 - STAG && c.wg != EARLYWG) {
          wgmma_wait<0>();
          if (STAG == R2) release2(c, prev);
          named_sync(4, 256);
        }
        stage2_kb<true>(c, acc, slot, ph, prev, i - 1 < n2 - R2 && !(STAG == R2 && c.wg != EARLYWG && i == n2 - STAG));
        prev = slot;
        if (++slot == R2) { slot = 0; ph ^= 1; }
      }
      if (STAG > 0 && c.wg == EARLYWG) named_arrive(4, 256);
      wgmma_wait<0>();
      fence_acc(acc);
      if (c.elect) TL(24 + c.wg);
      if (kh) stage2_finish<1>(c, acc, xr, outw);
      else    stage2_finish<0>(c, acc, xr, outw);

      if (c.elect) TL(28 + c.wg);
    }
  }
}

typedef CUresult (*PFN_encodeTiled)(CUtensorMap*, CUtensorMapDataType, cuuint32_t, void*, const cuuint64_t*, const cuuint64_t*,
                                    const cuuint32_t*, const cuuint32_t*, CUtensorMapInterleave, CUtensorMapSwizzle,
                                    CUtensorMapL2promotion, CUtensorMapFloatOOBfill);

void make_map(PFN_encodeTiled enc, CUtensorMap* m, const void* ptr, uint64_t rows, uint64_t cols, uint32_t box_rows, uint32_t box_cols, CUtensorMapSwizzle sw) {
  cuuint64_t dims[2] = {cols, rows};
  cuuint64_t strides[1] = {cols * 2};
  cuuint32_t box[2] = {box_cols, box_rows};
  cuuint32_t es[2] = {1, 1};
  enc(m, CU_TENSOR_MAP_DATA_TYPE_BFLOAT16, 2, const_cast<void*>(ptr), dims, strides, box, es, CU_TENSOR_MAP_INTERLEAVE_NONE, sw,
      CU_TENSOR_MAP_L2_PROMOTION_L2_256B, CU_TENSOR_MAP_FLOAT_OOB_FILL_NONE);
}
void make_map3(PFN_encodeTiled enc, CUtensorMap* m, const void* ptr, uint64_t rows, uint64_t cols, uint32_t box_rows, uint32_t box_cols, uint32_t nblk, CUtensorMapSwizzle sw) {
  cuuint64_t dims[3] = {box_cols, rows, cols / box_cols};
  cuuint64_t strides[2] = {cols * 2, (cuuint64_t)box_cols * 2};
  cuuint32_t box[3] = {box_cols, box_rows, nblk};
  cuuint32_t es[3] = {1, 1, 1};
  enc(m, CU_TENSOR_MAP_DATA_TYPE_BFLOAT16, 3, const_cast<void*>(ptr), dims, strides, box, es, CU_TENSOR_MAP_INTERLEAVE_NONE, sw,
      CU_TENSOR_MAP_L2_PROMOTION_L2_256B, CU_TENSOR_MAP_FLOAT_OOB_FILL_NONE);
}

}

extern "C" void kernel_launch(void* const* d_in, const int* in_sizes, int n_in, void* d_out, int out_size) {
  (void)in_sizes; (void)n_in; (void)out_size;
  PFN_encodeTiled enc = nullptr;
  cudaDriverEntryPointQueryResult qres;
  cudaGetDriverEntryPoint("cuTensorMapEncodeTiled", (void**)&enc, cudaEnableDefault, &qres);
  Params p;
  p.x = (const __nv_bfloat16*)d_in[0]; p.out = (__nv_bfloat16*)d_out;
  cudaGetSymbolAddress((void**)&p.xn, g_xn); cudaGetSymbolAddress((void**)&p.cnt, g_cnt);
  cudaGetSymbolAddress((void**)&p.abT, g_abT); cudaGetSymbolAddress((void**)&p.hT, g_hT);
  p.dr = (const __nv_bfloat16*)d_in[3]; p.di = (const __nv_bfloat16*)d_in[4];
  p.wg = (const __nv_bfloat16*)d_in[6]; p.wu = (const __nv_bfloat16*)d_in[7]; p.wd = (const __nv_bfloat16*)d_in[8];
  Maps maps;
  make_map(enc, &maps.xn, p.xn, S_, D_, 128, 64, CU_TENSOR_MAP_SWIZZLE_128B);
  make_map(enc, &maps.dr, d_in[3], D_, D_, 128, 64, CU_TENSOR_MAP_SWIZZLE_128B);
  make_map(enc, &maps.di, d_in[4], D_, D_, 128, 64, CU_TENSOR_MAP_SWIZZLE_128B);
  make_map(enc, &maps.wg, d_in[6], D_, F_, 64, 64, CU_TENSOR_MAP_SWIZZLE_128B);
  make_map(enc, &maps.wu, d_in[7], D_, F_, 64, 64, CU_TENSOR_MAP_SWIZZLE_128B);
  make_map(enc, &maps.cr, d_in[1], S_, S_, 128, 64, CU_TENSOR_MAP_SWIZZLE_128B);
  make_map(enc, &maps.ci, d_in[2], S_, S_, 128, 64, CU_TENSOR_MAP_SWIZZLE_128B);
  make_map3(enc, &maps.h, p.hT, F_, S_, 64, 64, 2, CU_TENSOR_MAP_SWIZZLE_128B);
  make_map(enc, &maps.ab, p.abT, 2 * D_, S_, 80, 64, CU_TENSOR_MAP_SWIZZLE_128B);
  make_map3(enc, &maps.wd, d_in[8], F_, D_, 32, 32, 5, CU_TENSOR_MAP_SWIZZLE_64B);
  cudaFuncSetAttribute(fused_kernel, cudaFuncAttributeMaxDynamicSharedMemorySize, SMEM_BYTES);
  cudaLaunchConfig_t cfg = {};
  cfg.gridDim = dim3(NUM_CTAS); cfg.blockDim = dim3(384); cfg.dynamicSmemBytes = SMEM_BYTES; cfg.stream = cudaStreamPerThread;
  cudaLaunchAttribute at[1];
  at[0].id = cudaLaunchAttributeClusterDimension; at[0].val.clusterDim.x = 2; at[0].val.clusterDim.y = 1; at[0].val.clusterDim.z = 1;
  cfg.attrs = at; cfg.numAttrs = 1;
  cudaLaunchKernelEx(&cfg, fused_kernel, p, maps);
}
```

```cpp
#include <cuda_runtime.h>
#include <cuda_bf16.h>
#include <cuda.h>
#include <stdint.h>

template<int TA, int TB, int SA> __device__ __forceinline__ void wgmma_ss_n128(float (&d)[64], uint64_t da, uint64_t db, int sd) {
  asm volatile("{\n.reg .pred p;\nsetp.ne.b32 p, %66, 0;\n"
    "wgmma.mma_async.sync.aligned.m64n128k16.f32.bf16.bf16 {%0, %1, %2, %3, %4, %5, %6, %7, %8, %9, %10, %11, %12, %13, %14, %15, %16, %17, %18, %19, %20, %21, %22, %23, %24, %25, %26, %27, %28, %29, %30, %31, %32, %33, %34, %35, %36, %37, %38, %39, %40, %41, %42, %43, %44, %45, %46, %47, %48, %49, %50, %51, %52, %53, %54, %55, %56, %57, %58, %59, %60, %61, %62, %63}, %64, %65, p, %69, 1, %67, %68;\n}\n"
    : "+f"(d[0]), "+f"(d[1]), "+f"(d[2]), "+f"(d[3]), "+f"(d[4]), "+f"(d[5]), "+f"(d[6]), "+f"(d[7]), "+f"(d[8]), "+f"(d[9]), "+f"(d[10]), "+f"(d[11]), "+f"(d[12]), "+f"(d[13]), "+f"(d[14]), "+f"(d[15]), "+f"(d[16]), "+f"(d[17]), "+f"(d[18]), "+f"(d[19]), "+f"(d[20]), "+f"(d[21]), "+f"(d[22]), "+f"(d[23]), "+f"(d[24]), "+f"(d[25]), "+f"(d[26]), "+f"(d[27]), "+f"(d[28]), "+f"(d[29]), "+f"(d[30]), "+f"(d[31]), "+f"(d[32]), "+f"(d[33]), "+f"(d[34]), "+f"(d[35]), "+f"(d[36]), "+f"(d[37]), "+f"(d[38]), "+f"(d[39]), "+f"(d[40]), "+f"(d[41]), "+f"(d[42]), "+f"(d[43]), "+f"(d[44]), "+f"(d[45]), "+f"(d[46]), "+f"(d[47]), "+f"(d[48]), "+f"(d[49]), "+f"(d[50]), "+f"(d[51]), "+f"(d[52]), "+f"(d[53]), "+f"(d[54]), "+f"(d[55]), "+f"(d[56]), "+f"(d[57]), "+f"(d[58]), "+f"(d[59]), "+f"(d[60]), "+f"(d[61]), "+f"(d[62]), "+f"(d[63])
    : "l"(da), "l"(db), "r"(sd), "n"(TA), "n"(TB), "n"(SA));
}
template<int TA, int TB, int SA> __device__ __forceinline__ void wgmma_ss_n160(float (&d)[80], uint64_t da, uint64_t db, int sd) {
  asm volatile("{\n.reg .pred p;\nsetp.ne.b32 p, %82, 0;\n"
    "wgmma.mma_async.sync.aligned.m64n160k16.f32.bf16.bf16 {%0, %1, %2, %3, %4, %5, %6, %7, %8, %9, %10, %11, %12, %13, %14, %15, %16, %17, %18, %19, %20, %21, %22, %23, %24, %25, %26, %27, %28, %29, %30, %31, %32, %33, %34, %35, %36, %37, %38, %39, %40, %41, %42, %43, %44, %45, %46, %47, %48, %49, %50, %51, %52, %53, %54, %55, %56, %57, %58, %59, %60, %61, %62, %63, %64, %65, %66, %67, %68, %69, %70, %71, %72, %73, %74, %75, %76, %77, %78, %79}, %80, %81, p, %85, 1, %83, %84;\n}\n"
    : "+f"(d[0]), "+f"(d[1]), "+f"(d[2]), "+f"(d[3]), "+f"(d[4]), "+f"(d[5]), "+f"(d[6]), "+f"(d[7]), "+f"(d[8]), "+f"(d[9]), "+f"(d[10]), "+f"(d[11]), "+f"(d[12]), "+f"(d[13]), "+f"(d[14]), "+f"(d[15]), "+f"(d[16]), "+f"(d[17]), "+f"(d[18]), "+f"(d[19]), "+f"(d[20]), "+f"(d[21]), "+f"(d[22]), "+f"(d[23]), "+f"(d[24]), "+f"(d[25]), "+f"(d[26]), "+f"(d[27]), "+f"(d[28]), "+f"(d[29]), "+f"(d[30]), "+f"(d[31]), "+f"(d[32]), "+f"(d[33]), "+f"(d[34]), "+f"(d[35]), "+f"(d[36]), "+f"(d[37]), "+f"(d[38]), "+f"(d[39]), "+f"(d[40]), "+f"(d[41]), "+f"(d[42]), "+f"(d[43]), "+f"(d[44]), "+f"(d[45]), "+f"(d[46]), "+f"(d[47]), "+f"(d[48]), "+f"(d[49]), "+f"(d[50]), "+f"(d[51]), "+f"(d[52]), "+f"(d[53]), "+f"(d[54]), "+f"(d[55]), "+f"(d[56]), "+f"(d[57]), "+f"(d[58]), "+f"(d[59]), "+f"(d[60]), "+f"(d[61]), "+f"(d[62]), "+f"(d[63]), "+f"(d[64]), "+f"(d[65]), "+f"(d[66]), "+f"(d[67]), "+f"(d[68]), "+f"(d[69]), "+f"(d[70]), "+f"(d[71]), "+f"(d[72]), "+f"(d[73]), "+f"(d[74]), "+f"(d[75]), "+f"(d[76]), "+f"(d[77]), "+f"(d[78]), "+f"(d[79])
    : "l"(da), "l"(db), "r"(sd), "n"(TA), "n"(TB), "n"(SA));
}

namespace {

constexpr int S_ = 2048, D_ = 640, F_ = 1728;
constexpr int A_CHUNK   = 16384;
constexpr int RING1_OFF = 10 * A_CHUNK;
constexpr int R1        = 4;
constexpr int SLOT2     = 36864;
constexpr int R2        = 6;
constexpr int BAR_OFF   = RING1_OFF + R1 * 16384;
constexpr int TL_OFF    = BAR_OFF + 512;
constexpr int TL2_OFF = TL_OFF + 512;
constexpr int SMEM_BYTES = TL_OFF + 512 + 1024;
constexpr int NUM_CTAS  = 132;
#define NC1 38
#define ND1 13
#define MAPV 1
#define REL1 0
#define REL2 0
#define FREE0 3
#define ZERO_NS 3500
#define PFKB 7
#define STAG 6
#define EARLYWG kh
#define XAHEAD 2
#define XW 1
#define PFW 9
#define KHA 1
#define EXP_ST 0
#define EXP_NOX 0
#define PACE_AB 70
#define PACE_H 0
#define PACE_Z 50
#define XEARLY 1
#define HLOOP 1
#define EXP_TAIL 0
#define CPF 0
#define CPF_START 2000
#define CPF_KH0 3000
#define CPF_GAP 800
#define CPF_FIRST 0
#define RPF 0
#define SILU_ORD 0
#define EARLY_ARV 0
#define PF 0

__device__ __nv_bfloat16 g_xn[S_ * D_];
__device__ __nv_bfloat16 g_abT[2 * D_ * S_];
__device__ __nv_bfloat16 g_hT[F_ * S_];
constexpr int CNT_XN = 0, CNT_H = 16, CNT_HX = 32, CNT_A = 48, CNT_B = 49, CNT_DONE = 50, CNT_TOTAL = 51;
__device__ unsigned g_cnt[CNT_TOTAL * 32];
#define T2(idx) do {} while (0)
#define TL(idx) do {} while (0)

struct Params {
  const __nv_bfloat16* x; __nv_bfloat16* out;
  __nv_bfloat16* xn; unsigned* cnt; __nv_bfloat16* abT; __nv_bfloat16* hT;
  const __nv_bfloat16 *dr, *di, *wg, *wu, *wd, *cr, *ci;
};
struct Maps {
  CUtensorMap xn, dr, di, wg, wu, cr, ci, h, ab, wd;
};

__device__ __forceinline__ uint32_t smem_u32(const void* p) { return (uint32_t)__cvta_generic_to_shared(p); }
__device__ __forceinline__ void mbar_init(uint32_t bar, uint32_t count) { asm volatile("mbarrier.init.shared::cta.b64 [%0], %1;" :: "r"(bar), "r"(count)); }
__device__ __forceinline__ void mbar_expect_tx(uint32_t bar, uint32_t bytes) { asm volatile("mbarrier.arrive.expect_tx.shared::cta.b64 _, [%0], %1;" :: "r"(bar), "r"(bytes) : "memory"); }
__device__ __forceinline__ void mbar_arrive(uint32_t bar) { asm volatile("mbarrier.arrive.shared::cta.b64 _, [%0];" :: "r"(bar) : "memory"); }
__device__ __forceinline__ void mbar_arrive_cta(uint32_t bar, uint32_t cta) {
  asm volatile("{\n.reg .b32 ra;\nmapa.shared::cluster.u32 ra, %0, %1;\nmbarrier.arrive.shared::cluster.b64 _, [ra];\n}\n" :: "r"(bar), "r"(cta) : "memory");
}
__device__ __forceinline__ void mbar_arrive_if(uint32_t bar, uint32_t pred) {
  asm volatile("{\n.reg .pred p;\nsetp.ne.u32 p, %1, 0;\n@p mbarrier.arrive.shared::cta.b64 _, [%0];\n}\n" :: "r"(bar), "r"(pred) : "memory");
}
__device__ __forceinline__ void mbar_arrive_cta_if(uint32_t bar, uint32_t cta, uint32_t pred) {
  asm volatile("{\n.reg .pred p;\n.reg .b32 ra;\nsetp.ne.u32 p, %2, 0;\nmapa.shared::cluster.u32 ra, %0, %1;\n@p mbarrier.arrive.shared::cluster.b64 _, [ra];\n}\n" :: "r"(bar), "r"(cta), "r"(pred) : "memory");
}
__device__ __forceinline__ void mbar_wait(uint32_t bar, uint32_t parity) {
  asm volatile("{\n.reg .pred p;\n.reg .u32 n;\nmov.u32 n, 0;\n"
    "LAB_WAIT:\n"
    "mbarrier.try_wait.parity.shared::cta.b64 p, [%0], %1;\n"
    "@p bra LAB_DONE;\n"
    "add.u32 n, n, 1;\n"
    "setp.lt.u32 p, n, 4000000;\n"
    "@p bra LAB_WAIT;\n"
    "trap;\n"
    "LAB_DONE:\n}\n" :: "r"(bar), "r"(parity) : "memory");
}
__device__ __forceinline__ void tma_load(uint32_t dst, const CUtensorMap* map, int c0, int c1, uint32_t bar) {
  asm volatile("cp.async.bulk.tensor.2d.shared::cluster.global.mbarrier::complete_tx::bytes [%0], [%1, {%3, %4}], [%2];"
    :: "r"(dst), "l"(map), "r"(bar), "r"(c0), "r"(c1) : "memory");
}
__device__ __forceinline__ void tma_load_mc(uint32_t dst, const CUtensorMap* map, int c0, int c1, uint32_t bar) {
  asm volatile("cp.async.bulk.tensor.2d.shared::cluster.global.mbarrier::complete_tx::bytes.multicast::cluster [%0], [%1, {%3, %4}], [%2], %5;"
    :: "r"(dst), "l"(map), "r"(bar), "r"(c0), "r"(c1), "h"((uint16_t)3) : "memory");
}
__device__ __forceinline__ void tma_load_3d(uint32_t dst, const CUtensorMap* map, int c1, int c2, uint32_t bar) {
  asm volatile("cp.async.bulk.tensor.3d.shared::cluster.global.mbarrier::complete_tx::bytes [%0], [%1, {%5, %3, %4}], [%2];"
    :: "r"(dst), "l"(map), "r"(bar), "r"(c1), "r"(c2), "r"(0) : "memory");
}
__device__ __forceinline__ void tma_load_3d_mc(uint32_t dst, const CUtensorMap* map, int c1, int c2, uint32_t bar) {
  asm volatile("cp.async.bulk.tensor.3d.shared::cluster.global.mbarrier::complete_tx::bytes.multicast::cluster [%0], [%1, {%5, %3, %4}], [%2], %6;"
    :: "r"(dst), "l"(map), "r"(bar), "r"(c1), "r"(c2), "r"(0), "h"((uint16_t)3) : "memory");
}
__device__ __forceinline__ void tma_prefetch(const CUtensorMap* map, int c0, int c1) {
  asm volatile("cp.async.bulk.prefetch.tensor.2d.L2.global [%0, {%1, %2}];" :: "l"(map), "r"(c0), "r"(c1) : "memory");
}
__device__ __forceinline__ void prefetch_map(const CUtensorMap* map) { asm volatile("prefetch.tensormap [%0];" :: "l"(map) : "memory"); }
__device__ __forceinline__ void l2_prefetch(const void* p, uint32_t bytes) { asm volatile("cp.async.bulk.prefetch.L2.global [%0], %1;" :: "l"(p), "r"(bytes) : "memory"); }
__device__ __forceinline__ void wgmma_fence() { asm volatile("wgmma.fence.sync.aligned;" ::: "memory"); }
__device__ __forceinline__ void wgmma_commit() { asm volatile("wgmma.commit_group.sync.aligned;" ::: "memory"); }
template<int N> __device__ __forceinline__ void wgmma_wait() { asm volatile("wgmma.wait_group.sync.aligned %0;" :: "n"(N) : "memory"); }
template<int N> __device__ __forceinline__ void fence_acc(float (&d)[N]) {
  #pragma unroll
  for (int i = 0; i < N; i++) asm volatile("" : "+f"(d[i]) :: "memory");
}
__device__ __forceinline__ void named_sync(int id, int n) { asm volatile("bar.sync %0, %1;" :: "r"(id), "r"(n) : "memory"); }
__device__ __forceinline__ void named_arrive(int id, int n) { asm volatile("bar.arrive %0, %1;" :: "r"(id), "r"(n) : "memory"); }
template<int R> __device__ __forceinline__ void reg_alloc() { asm volatile("setmaxnreg.inc.sync.aligned.u32 %0;" :: "n"(R)); }
template<int R> __device__ __forceinline__ void reg_dealloc() { asm volatile("setmaxnreg.dec.sync.aligned.u32 %0;" :: "n"(R)); }
__device__ __forceinline__ void fence_proxy_async_global() { asm volatile("fence.proxy.async.global;" ::: "memory"); }
#define WFENCE fence_proxy_async_global()
#define PFENCE fence_proxy_async_global()
template<int NS> __device__ __forceinline__ void pace() { if (NS > 0) asm volatile("nanosleep.u32 %0;" :: "n"(NS) : "memory"); }
__device__ __forceinline__ void red_release(unsigned* p) { asm volatile("red.release.gpu.global.add.u32 [%0], 1;" :: "l"(p) : "memory"); }
__device__ __forceinline__ void red_relaxed(unsigned* p) { asm volatile("red.relaxed.gpu.global.add.u32 [%0], 1;" :: "l"(p) : "memory"); }
#define PUB_RED red_release
template<int SLEEP_NS>
__device__ __forceinline__ void wait_counter(const unsigned* p, unsigned target) {
  asm volatile("{\n.reg .pred p;\n.reg .u32 n, v;\nmov.u32 n, 0;\n"
    "LAB_WAIT:\n"
    "ld.acquire.gpu.global.u32 v, [%0];\n"
    "setp.ge.u32 p, v, %1;\n"
    "@p bra LAB_DONE;\n"
    "nanosleep.u32 %2;\n"
    "add.u32 n, n, 1;\n"
    "setp.lt.u32 p, n, 2000000;\n"
    "@p bra LAB_WAIT;\n"
    "trap;\n"
    "LAB_DONE:\n}\n" :: "l"(p), "r"(target), "n"(SLEEP_NS) : "memory");
}
constexpr uint32_t HI_SW128 = (1024 >> 4) | (1u << 30);
constexpr uint32_t HI_SW64  = (512 >> 4) | (2u << 30);
constexpr uint32_t DBASE    = 0x400 >> 4;
constexpr uint32_t LBO_NONE = 1u << 16;
constexpr uint32_t LBO_2K   = (2048u >> 4) << 16;
__device__ __forceinline__ uint64_t mk_desc(uint32_t lo, uint32_t hi) { uint64_t d; asm("mov.b64 %0, {%1, %2};" : "=l"(d) : "r"(lo), "r"(hi)); return d; }

__device__ __forceinline__ uint32_t pack_bf16(float lo, float hi) {
  uint32_t r; asm("cvt.rn.bf16x2.f32 %0, %1, %2;" : "=r"(r) : "f"(hi), "f"(lo)); return r;
}
__device__ __forceinline__ float bf_lo(uint32_t v) { return __uint_as_float(v << 16); }
__device__ __forceinline__ float bf_hi(uint32_t v) { return __uint_as_float(v & 0xffff0000u); }
__device__ __forceinline__ float round_bf(float v) { return bf_lo(pack_bf16(v, 0.f)); }
__device__ __forceinline__ uint32_t norm2(uint32_t x, uint32_t m2, uint32_t ih2, uint32_t il2) {
  uint32_t d, t, r;
  asm("sub.rn.bf16x2 %0, %1, %2;" : "=r"(d) : "r"(x), "r"(m2));
  asm("mul.rn.bf16x2 %0, %1, %2;" : "=r"(t) : "r"(d), "r"(il2));
  asm("fma.rn.bf16x2 %0, %1, %2, %3;" : "=r"(r) : "r"(d), "r"(ih2), "r"(t));
  return r;
}
__device__ __forceinline__ float silu_mul(float g, float u, float nl2e = -1.4426950408889634f) {
  float e, r;
  asm("ex2.approx.ftz.f32 %0, %1;" : "=f"(e) : "f"(g * nl2e));
  asm("rcp.approx.ftz.f32 %0, %1;" : "=f"(r) : "f"(e + 1.0f));
  return (g * u) * r;
}
__device__ __forceinline__ int xn_row(int t) { return (t & ~30) | ((t & 6) << 2) | ((t & 24) >> 2); }
__device__ __forceinline__ int unit_of(int role, int t) {
  const int two_ab = (role & 5) == 0;
  if (t == 0) return role;
  if (t == 1 && two_ab) return 8 + (role >> 1);
  return 9 + 3 * role + (role > 4) + (role > 6) + t - two_ab;
}

__device__ __forceinline__ void prefetch_unit(const Maps& maps, int unit, int kb) {
  if (unit < 10) tma_prefetch(unit < 5 ? &maps.dr : &maps.di, kb * 64, (unit < 5 ? unit : unit - 5) * 128);
  else { tma_prefetch(&maps.wg, (unit - 10) * 64, kb * 64); tma_prefetch(&maps.wu, (unit - 10) * 64, kb * 64); }
}

struct Ctx {
  uint32_t sbase, full1, empty1, full2, empty2, flagb, pub, xfull;
  int wg, warp, lane, zero;
  bool elect;
};

template<int MODE, bool LAST>
__device__ __forceinline__ void stage1_mma(const Ctx& c, float (&acc)[2][64], int it0, bool first, bool has_next, bool free_all) {
  int prev = 0;
  #pragma unroll 1
  for (int kb = 0; kb < 10; kb++) {
    const int it = it0 + kb;
    const int slot = it & 3;
    const uint32_t bx = DBASE + kb * (A_CHUNK >> 4) + LBO_NONE;
    const uint32_t ar = DBASE + slot * 1024 + ((RING1_OFF >> 4) + LBO_NONE);
    const uint32_t rel = c.elect && kb > 0, rel2 = c.elect && kb >= 3 && (kb & 1);
    if (MODE != 2 && first) mbar_wait(c.xfull + 8 * kb, 0);
    mbar_wait(c.full1 + 8 * slot, (it >> 2) & 1);
    if (kb == 9 && has_next) named_arrive(1 + (c.wg ^ 1), 256);
    wgmma_fence();
    #pragma unroll
    for (int k = 0; k < 4; k++) {
      #pragma unroll
      for (int i = 0; i < 2; i++) {
        if (MODE == 2) wgmma_ss_n128<1, 0, 1>(acc[i], mk_desc(ar + i * 512 + k * 128, HI_SW128), mk_desc(bx + k * 2, HI_SW128), (kb | k) != 0);
        else           wgmma_ss_n128<0, 0, (MODE == 1 ? -1 : 1)>(acc[i], mk_desc(ar + i * 512 + k * 2, HI_SW128), mk_desc(bx + k * 2, HI_SW128), (kb | k) != 0);
      }
      if (k == 0) {
        wgmma_commit();
        wgmma_wait<1>();
        if (c.elect) T2(it + it0 / 10);
        mbar_arrive_if(c.empty1 + 8 * prev, rel);
        wgmma_fence();
      }
      if (LAST && (k == 1 || k == 2)) mbar_arrive_cta_if(c.empty2 + 4 * (kb - 3), k - 1, rel2);
    }
    wgmma_commit();
    prev = slot;
  }
  #pragma unroll 1
  for (int z = c.zero; z < 1; z++) {
    wgmma_wait<0>();
    if (c.elect) {
      mbar_arrive(c.empty1 + 8 * prev);
      TL(33 + (it0 / 10) * 4); T2(it0 + 10 + it0 / 10);
      if (LAST || free_all) {
        #pragma unroll
        for (int j = LAST ? 4 : 0; j < R2; j++) { mbar_arrive_cta(c.empty2 + 8 * j, 0); mbar_arrive_cta(c.empty2 + 8 * j, 1); }
      }
    }
  }
  wgmma_wait<0>();
  fence_acc(acc[0]); fence_acc(acc[1]);
}
#define ST_AB(dst, i, hf, J) if (EXP_ST == 0 || acc[0][0] == 1.2345f) dst[((i) * 64 + (hf) * 8) * (S_ / 8) + (J) * 4] =
#define ST_H(dst, hf, J) if (EXP_ST == 0 || w[0] == 0x12345) dst[(hf) * 8 * (S_ / 8) + (J) * 4] =
#define ROWOFF(u, rl, col) ((size_t)((u) + (rl)) * S_ + (col))
__device__ __forceinline__ void store_ab(const float (&acc)[2][64], uint4* dst) {
  #pragma unroll
  for (int i = 0; i < 2; i++)
    #pragma unroll
    for (int hf = 0; hf < 2; hf++)
      #pragma unroll
      for (int J = 0; J < 4; J++) {
        const int r = 16 * J + 2 * hf;
        ST_AB(dst, i, hf, J) make_uint4(pack_bf16(acc[i][r], acc[i][r + 1]), pack_bf16(acc[i][r + 4], acc[i][r + 5]),
                                                               pack_bf16(acc[i][r + 8], acc[i][r + 9]), pack_bf16(acc[i][r + 12], acc[i][r + 13]));
        if (i + hf + J < 5) pace<PACE_AB>();
      }
}
__device__ __forceinline__ void store_h_slice(const float (&acc)[2][64], uint4* dst, int sl, float nl2e) {
  const int hf = sl >> 2, J = sl & 3;
  uint32_t w[4];
  #pragma unroll
  for (int b = 0; b < 4; b++) {
    const int r = 16 * J + 4 * b + 2 * hf;
    w[b] = pack_bf16(silu_mul(acc[0][r], acc[1][r], nl2e), silu_mul(acc[0][r + 1], acc[1][r + 1], nl2e));
  }
  ST_H(dst, hf, J) make_uint4(w[0], w[1], w[2], w[3]);
}
__device__ __forceinline__ void publish(const Ctx& c, int t) {
  if (c.elect) TL(34 + t * 4);
  __syncwarp();
  if (c.lane == 0) mbar_arrive(c.pub + 8 * t);
}
__device__ __forceinline__ void release2(const Ctx& c, int slot) {
  if (c.elect) { mbar_arrive_cta(c.empty2 + 8 * slot, 0); mbar_arrive_cta(c.empty2 + 8 * slot, 1); }
}
template<bool DPART>
__device__ __forceinline__ void stage2_kb(const Ctx& c, float (&acc)[80], int slot, int ph, int prev, bool rel, int ii) {
  const uint32_t sa = DBASE + slot * (SLOT2 >> 4) + c.wg * 512 + LBO_NONE, sb = DBASE + slot * (SLOT2 >> 4) + (1024 + (DPART ? LBO_2K : LBO_NONE));
  mbar_wait(c.full2 + 8 * slot, ph);
  wgmma_fence();
  #pragma unroll
  for (int k = 0; k < 4; k++) {
    if (DPART) wgmma_ss_n160<1, 1, 1>(acc, mk_desc(sa + k * 128, HI_SW128), mk_desc(sb + (k >> 1) * 640 + (k & 1) * 64, HI_SW64), 1);
    else       wgmma_ss_n160<0, 0, 1>(acc, mk_desc(sa + k * 2, HI_SW128), mk_desc(sb + k * 2, HI_SW128), 1);
    if (k == REL2) {
      wgmma_commit();
      wgmma_wait<1>();
      if (c.elect) T2(64 + c.wg * 64 + ii);
      if (rel) release2(c, prev);
      if (k < 3) wgmma_fence();
    }
  }
  if (REL2 < 3) wgmma_commit();
}

struct OutAddr { uint32_t sw, lf, lh; char *gf, *gh; };
__device__ __forceinline__ uint32_t add_bf2(uint32_t a, uint32_t b) { uint32_t r; asm("add.rn.bf16x2 %0, %1, %2;" : "=r"(r) : "r"(a), "r"(b)); return r; }
__device__ __forceinline__ void stage2_finish(const float (&acc)[80], const OutAddr& o, const uint4 (&xr)[10], bool add_x) {
  if (EXP_TAIL == 1 && add_x && acc[0] != 1.2345f) return;
  #pragma unroll
  for (int jj = 0; jj < 10; jj++) {
    asm volatile("stmatrix.sync.aligned.m8n8.x4.shared.b16 [%0], {%1, %2, %3, %4};" :: "r"(o.sw + jj * 32),
                 "r"(pack_bf16(acc[8 * jj], acc[8 * jj + 1])), "r"(pack_bf16(acc[8 * jj + 2], acc[8 * jj + 3])),
                 "r"(pack_bf16(acc[8 * jj + 4], acc[8 * jj + 5])), "r"(pack_bf16(acc[8 * jj + 6], acc[8 * jj + 7])) : "memory");
  }
  __syncwarp();
  if (EXP_TAIL == 2 && add_x && acc[0] != 1.2345f) return;
  uint4 v[10];
  #pragma unroll
  for (int i = 0; i < 10; i++) {
    const uint32_t a = i < 8 ? o.lf + (i >> 1) * (4 * 336) + (i & 1) * 128 : o.lh + (i - 8) * (8 * 336);
    asm volatile("ld.shared.v4.u32 {%0, %1, %2, %3}, [%4];" : "=r"(v[i].x), "=r"(v[i].y), "=r"(v[i].z), "=r"(v[i].w) : "r"(a) : "memory");
  }
  if (add_x) {
    #pragma unroll
    for (int i = 0; i < 10; i++) { v[i].x = add_bf2(v[i].x, xr[i].x); v[i].y = add_bf2(v[i].y, xr[i].y); v[i].z = add_bf2(v[i].z, xr[i].z); v[i].w = add_bf2(v[i].w, xr[i].w); }
  }
  if (EXP_TAIL == 3 && add_x && v[0].x != 0x12345) return;
  #pragma unroll
  for (int i = 0; i < 10; i++) {
    char* g = i < 8 ? o.gf + (i >> 1) * (4 * D_ * 2) + (i & 1) * 128 : o.gh + (i - 8) * (8 * D_ * 2);
    asm volatile("red.global.add.noftz.v4.bf16x2 [%0], {%1, %2, %3, %4};" :: "l"(g), "r"(v[i].x), "r"(v[i].y), "r"(v[i].z), "r"(v[i].w) : "memory");
  }
}

__global__ void __launch_bounds__(384, 1)
fused_kernel(const __grid_constant__ Params p, const __grid_constant__ Maps maps) {
  extern __shared__ __align__(1024) uint8_t smem_raw[];
  const int cl = blockIdx.x >> 1, rank = blockIdx.x & 1;
  const bool extra = cl >= 64;
  const int tok = (blockIdx.x & 127) * 16 + ((threadIdx.x >> 4) & 15), l16 = threadIdx.x & 15;
  uint4 v[5];
  uint32_t x0 = 0;
  if (threadIdx.x < 256) {
    const uint4* xs = reinterpret_cast<const uint4*>(p.x + (size_t)tok * D_);
    #pragma unroll
    for (int i = 0; i < 5; i++) v[i] = __ldg(xs + l16 + 16 * i);
    x0 = __ldg(reinterpret_cast<const uint32_t*>(xs));
  }
  int kh, nt, grp;
  {
    int pos, half;
    if (cl >= 4 && cl < 36) { half = 0; pos = (cl - 4) & 7; nt = (cl - 4) >> 3; }
    else if (cl >= 36)      { half = 1; nt = (cl - 36) / 7; pos = 1 + (cl - 36) - nt * 7; nt &= 3; }
    else                    { half = 1; pos = 0; nt = cl; }
    kh = (pos >> 2) ^ KHA ^ 1; grp = (pos & 3) * 2 + half;
  }
  const int mb2 = grp * 2 + rank;
  const int role = kh + 2 * ((nt & 1) * 2 + rank);
  const int mb1 = extra ? (cl - 64) * 8 + rank : grp * 2 + (nt >> 1);

  Ctx c;
  c.sbase = __shfl_sync(0xffffffffu, smem_u32(smem_raw), 0);
  c.zero = __shfl_sync(0xffffffffu, threadIdx.x >> 10, 0);
  c.full1 = c.sbase + BAR_OFF; c.empty1 = c.full1 + 8 * R1; c.full2 = c.empty1 + 8 * R1; c.empty2 = c.full2 + 8 * R2;
  c.flagb = c.empty2 + 8 * R2; c.pub = c.flagb + 8 * 4; c.xfull = c.pub + 8 * 5;
  c.wg = __shfl_sync(0xffffffffu, threadIdx.x >> 7, 0);
  c.warp = __shfl_sync(0xffffffffu, (threadIdx.x >> 5) & 3, 0);
  c.lane = threadIdx.x & 31;
  c.elect = (threadIdx.x & 127) == 0;

  const int nT = extra ? 4 : 5 - kh;
  const int nC = kh ? NC1 : 64 - NC1, c0 = kh ? 0 : NC1, nD = kh ? ND1 : 27 - ND1, d0 = kh ? 0 : ND1;
  const int n2 = nC + nD;

  if (c.wg == 2) {
    reg_dealloc<40>();
    int wlo = c.warp & 1, whi = c.warp >> 1;
    asm volatile("" : "+r"(wlo)); asm volatile("" : "+r"(whi));
    const bool w0 = !whi && !wlo, w1 = !whi && wlo, w2 = whi && !wlo;
    if (c.lane == 0) {
      if (w0) {
        #pragma unroll
        for (int i = 0; i < 2 * R1; i++) mbar_init(c.full1 + 8 * i, 1);
      } else if (w1) {
        prefetch_map(&maps.xn);
        #pragma unroll
        for (int i = 0; i < 10; i++) mbar_init(c.xfull + 8 * i, 1);
      } else if (w2) {
        #pragma unroll
        for (int i = 0; i < R2; i++) { mbar_init(c.full2 + 8 * i, 1); mbar_init(c.empty2 + 8 * i, 4); }
      } else {
        #pragma unroll
        for (int i = 0; i < 4; i++) mbar_init(c.flagb + 8 * i, 1);
        #pragma unroll
        for (int i = 0; i < 5; i++) mbar_init(c.pub + 8 * i, 4);
        if ((c.sbase & 0x3FFFFu) != 0x400u) asm volatile("trap;");
      }
      asm volatile("fence.mbarrier_init.release.cluster;" ::: "memory");
      if (w0) TL(11);
    }
    __syncwarp();
    asm volatile("barrier.cluster.arrive.relaxed.aligned;" ::: "memory");
    asm volatile("barrier.cluster.wait.acquire.aligned;" ::: "memory");
    if (w0) {
      if (c.lane == 0) {
        int it = 0;
        for (int t = 0; t < nT; t++) {
          const int unit = extra ? 36 : unit_of(role, t);
          for (int kb = 0; kb < 10; kb++, it++) {
            const int slot = it & 3;
            const uint32_t full = c.full1 + 8 * slot;
            const uint32_t dst = c.sbase + RING1_OFF + slot * 16384;
            mbar_wait(c.empty1 + 8 * slot, ((it >> 2) & 1) ^ 1);
            mbar_expect_tx(full, extra ? 32768 : 16384);
            if (unit < 10) {
              tma_load(dst, unit < 5 ? &maps.dr : &maps.di, kb * 64, (unit < 5 ? unit : unit - 5) * 128, full);
            } else {
              tma_load(dst, &maps.wg, (unit - 10) * 64, kb * 64, full);
              tma_load(dst + 8192, &maps.wu, (unit - 10) * 64, kb * 64, full);
            }
            if (it == 3) { TL(12); prefetch_map(&maps.wg); prefetch_map(&maps.wu); prefetch_map(&maps.di); }
            if (kb == PFKB && t + 2 < nT && !extra && mb1 < 10) prefetch_unit(maps, unit_of(role, t + 2), mb1);
            if (extra) {
              if (kb == 0) { wait_counter<100>(&p.cnt[(CNT_XN + mb1 + 2 * t) * 32], 8); fence_proxy_async_global(); }
              tma_load(c.sbase + kb * A_CHUNK, &maps.xn, kb * 64, (mb1 + 2 * t) * 128, full);
            }
          }
        }
      }
    } else if (w1) {
      if (c.lane == 0 && !extra) {
        #pragma unroll
        for (int i = 0; i < 10; i++) mbar_expect_tx(c.xfull + 8 * i, A_CHUNK);
        wait_counter<0>(&p.cnt[(CNT_XN + mb1) * 32], 8);
        fence_proxy_async_global();
        TL(1);
        #pragma unroll
        for (int i = 0; i < 5; i++) {
          if (i >= XAHEAD) mbar_wait(c.xfull + 8 * (2 * (i - XAHEAD) + XW), 0);
          tma_load_mc(c.sbase + (2 * i + rank) * A_CHUNK, &maps.xn, (2 * i + rank) * 64, mb1 * 128, c.xfull + 8 * (2 * i + rank));
        }
        if (PFW >= 0) mbar_wait(c.xfull + 8 * PFW, 0);
        TL(14);
        if (mb1 < 10) prefetch_unit(maps, unit_of(role, 1), mb1);
        prefetch_map(&maps.cr); prefetch_map(&maps.ci); prefetch_map(&maps.ab); prefetch_map(&maps.h); prefetch_map(&maps.wd);
        int slot = 0, ph = 0;
        for (int i = 0; i < n2; i++) {
          if (PF > 0 && ((i + PF) & 3) == nt && i + PF < nC) { const int kc = c0 + i + PF; tma_prefetch(kc >= 32 ? &maps.ci : &maps.cr, (kc & 31) * 64, mb2 * 128); }
          const uint32_t full = c.full2 + 8 * slot;
          const uint32_t dst = c.sbase + slot * SLOT2;
          mbar_wait(c.empty2 + 8 * slot, ph);
          if (i == 0) { TL(2); mbar_wait(c.flagb, 0); PFENCE; TL(3); }
          if (c0 + i == max(c0, 32)) { mbar_wait(c.flagb + 24, 0); PFENCE; }
          mbar_expect_tx(full, SLOT2);
          if (i < nC) {
            const int kc = c0 + i;
            const int im = kc >= 32;
            const int kk = (kc & 31) * 64;
            tma_load(dst, im ? &maps.ci : &maps.cr, kk, mb2 * 128, full);
            tma_load_mc(dst + 16384 + rank * 10240, &maps.ab, kk, im * 640 + nt * 160 + rank * 80, full);
          } else {
            const int kd = d0 + i - nC;
            tma_load_3d_mc(dst + 16384 + rank * 10240, &maps.wd, kd * 64 + rank * 32, nt * 5, full);
            if (i == nC) { TL(4); mbar_wait(c.flagb + 8, 0); PFENCE; TL(5); }
            if (kd == 26) { mbar_wait(c.flagb + 16, 0); PFENCE; }
            tma_load_3d(dst, &maps.h, kd * 64, mb2 * 2, full);
          }
          if (++slot == R2) { slot = 0; ph ^= 1; }
        }
      }
    } else if (w2) {
      const uint32_t total = D_ * F_ * 2, per = ((total + NUM_CTAS - 1) / NUM_CTAS + 127) & ~127u, beg = blockIdx.x * per;
      if (c.lane == 0 && !extra && mb1 < 6) prefetch_unit(maps, role, 4 + mb1);
      __nanosleep(ZERO_NS);
      if (!extra) {
        char* zb = reinterpret_cast<char*>(p.out + (size_t)(mb2 * 128 + kh * 64) * D_ + nt * 160);
        char* zf = zb + (c.lane >> 3) * (D_ * 2) + (nt & 1) * 64 + (c.lane & 7) * 16;
        char* zh = zb + (c.lane >> 2) * (D_ * 2) + ((nt & 1) ^ 1) * 256 + (c.lane & 3) * 16;
        #pragma unroll
        for (int j = 0; j < 32; j++) { asm volatile("st.global.v4.u32 [%0], {%1, %1, %1, %1};" :: "l"(zf + (j >> 1) * (4 * D_ * 2) + (j & 1) * 128), "r"(0) : "memory"); pace<PACE_Z>(); }
        #pragma unroll
        for (int j = 0; j < 8; j++) { asm volatile("st.global.v4.u32 [%0], {%1, %1, %1, %1};" :: "l"(zh + j * (8 * D_ * 2)), "r"(0) : "memory"); pace<PACE_Z>(); }
      }
      __syncwarp();
      if (c.lane == 1) {
        __nanosleep(6000);
        if (beg < total) l2_prefetch((const char*)p.wd + beg, min(per, total - beg));
      } else if (c.lane == 0) {
        for (int t = 0; t < nT; t++) {
          mbar_wait(c.pub + 8 * t, 0);
          const int unit = unit_of(role, t);
          PUB_RED(&p.cnt[(extra ? CNT_HX + mb1 + 2 * t : unit < 5 ? CNT_A : unit < 10 ? CNT_B : CNT_H + mb1) * 32]);
          TL(35 + t * 4);
        }
      }
    } else {
      if (!extra) {
        named_sync(3, 256 + 32);
        if (c.lane == 0) {
          red_release(&p.cnt[(CNT_XN + (blockIdx.x >> 3)) * 32]);
          TL(55);
          __nanosleep(5000);
          wait_counter<300>(&p.cnt[CNT_A * 32], 80);           WFENCE; mbar_arrive(c.flagb);
          wait_counter<300>(&p.cnt[CNT_B * 32], 80);           WFENCE; mbar_arrive(c.flagb + 24);
          wait_counter<500>(&p.cnt[(CNT_H + mb2) * 32], 26);   WFENCE; mbar_arrive(c.flagb + 8);
          wait_counter<500>(&p.cnt[(CNT_HX + mb2) * 32], 1);   WFENCE; mbar_arrive(c.flagb + 16);
          if (atomicAdd(&p.cnt[CNT_DONE * 32], 1u) == 127u) {
            for (int i = 0; i < CNT_TOTAL; i++) p.cnt[i * 32] = 0;
          }
        }
      }
    }
  } else {
    asm volatile("barrier.cluster.arrive.relaxed.aligned;" ::: "memory");
    if (!extra) {
      const float sh = bf_lo(x0);
      float s0 = 0.f, s1 = 0.f, q0 = 0.f, q1 = 0.f;
      #pragma unroll
      for (int i = 0; i < 5; i++) {
        const uint32_t w[4] = {v[i].x, v[i].y, v[i].z, v[i].w};
        #pragma unroll
        for (int j = 0; j < 4; j++) { const float a = bf_lo(w[j]) - sh, b = bf_hi(w[j]) - sh; s0 += a; s1 += b; q0 = fmaf(a, a, q0); q1 = fmaf(b, b, q1); }
      }
      float s = s0 + s1, ss = q0 + q1;
      #pragma unroll
      for (int o = 1; o < 16; o <<= 1) { s += __shfl_xor_sync(0xffffffffu, s, o); ss += __shfl_xor_sync(0xffffffffu, ss, o); }
      const float dm = s * (1.0f / D_);
      const float var = fmaxf(fmaf(-dm, dm, ss * (1.0f / D_)), 0.f);
      float sd, inv;
      asm("sqrt.approx.f32 %0, %1;" : "=f"(sd) : "f"(round_bf(round_bf(var) + 1e-5f)));
      asm("rcp.approx.f32 %0, %1;" : "=f"(inv) : "f"(round_bf(sd)));
      const float ih = round_bf(inv);
      const uint32_t m2 = pack_bf16(sh + dm, sh + dm), ih2 = pack_bf16(ih, ih), il2 = pack_bf16(inv - ih, inv - ih);
      uint4* dst = reinterpret_cast<uint4*>(p.xn + (size_t)xn_row(tok) * D_);
      #pragma unroll
      for (int i = 0; i < 5; i++)
        dst[l16 + 16 * i] = make_uint4(norm2(v[i].x, m2, ih2, il2), norm2(v[i].y, m2, ih2, il2), norm2(v[i].z, m2, ih2, il2), norm2(v[i].w, m2, ih2, il2));
      named_arrive(3, 256 + 32);
    }
    reg_alloc<232>();
    asm volatile("barrier.cluster.wait.acquire.aligned;" ::: "memory");
    if (threadIdx.x == 0) TL(54);

    const int rl = c.warp * 16 + (c.lane >> 2);
    const int nT1 = extra ? nT : nT - 1;
    #pragma unroll 1
    for (int t = c.wg; t < nT1; t += 2) {
      const int unit = extra ? 36 : unit_of(role, t);
      const int col = (extra ? mb1 + 2 * t : mb1) * 128 + (c.lane & 3) * 8;
      if (t > 0) named_sync(1 + c.wg, 256);
      const bool free_all = !extra && t == nT - 2;
      const bool has_next = t < nT - 1;
      float acc[2][64];
      if (unit < 10) {
        if (unit < 5) stage1_mma<0, false>(c, acc, t * 10, t == 0, has_next, free_all);
        else          stage1_mma<1, false>(c, acc, t * 10, t == 0, has_next, free_all);
        store_ab(acc, reinterpret_cast<uint4*>(p.abT + ROWOFF(unit * 128, rl, col)));
      } else {
        stage1_mma<2, false>(c, acc, t * 10, false, has_next, free_all);
        uint4* dst = reinterpret_cast<uint4*>(p.hT + ROWOFF((unit - 10) * 64, rl, col));
        #pragma unroll
        for (int sl = 0; sl < 8; sl++) {
          #pragma unroll 1
          for (int z = c.zero; z < 1; z++) store_h_slice(acc, dst, sl, __int_as_float(0xbfb8aa3b + z));
          if (sl < 7) pace<PACE_H>();
        }
      }
      publish(c, t);
    }

    if (!extra) {
      OutAddr o;
      uint4 xr[10];
      {
        const uint32_t stg = c.sbase + c.warp * SLOT2 + c.wg * 8192;
        const int rf = c.lane >> 3, cf = (nt & 1) * 64 + (c.lane & 7) * 16;
        const int rh = (c.lane >> 3) + (c.lane & 4), ch = ((nt & 1) ^ 1) * 256 + (c.lane & 3) * 16;
        const size_t ob = ((size_t)(mb2 * 128 + c.wg * 64 + c.warp * 16) * D_ + nt * 160) * 2;
        o.sw = stg + (c.lane & 15) * 336 + (c.lane >> 4) * 16;
        o.lf = stg + rf * 336 + cf; o.lh = stg + rh * 336 + ch;
        o.gf = reinterpret_cast<char*>(p.out) + ob + rf * (D_ * 2) + cf; o.gh = reinterpret_cast<char*>(p.out) + ob + rh * (D_ * 2) + ch;
        asm volatile("" : "+r"(o.sw), "+r"(o.lf), "+r"(o.lh), "+l"(o.gf), "+l"(o.gh));
        const char* xf = reinterpret_cast<const char*>(p.x) + ob + rf * (D_ * 2) + cf;
        const char* xh = reinterpret_cast<const char*>(p.x) + ob + rh * (D_ * 2) + ch;
        #pragma unroll
        for (int i = 0; i < 10; i++) xr[i] = make_uint4(0u, 0u, 0u, 0u);
        if (c.wg == EARLYWG) {
          #pragma unroll
          for (int i = 0; i < 10; i++) xr[i] = __ldg(reinterpret_cast<const uint4*>(i < 8 ? xf + (i >> 1) * (4 * D_ * 2) + (i & 1) * 128 : xh + (i - 8) * (8 * D_ * 2)));
        }
      }
      float acc[80];
      int i0 = 0;
      if (((nT - 1) & 1) == c.wg) {
        const int t = nT - 1;
        named_sync(1 + c.wg, 256);
        uint32_t gu[2][32];
        {
          float acc1[2][64];
          stage1_mma<2, true>(c, acc1, t * 10, false, true, false);
          #pragma unroll
          for (int r = 0; r < 32; r++) { gu[0][r] = pack_bf16(acc1[0][2 * r], acc1[0][2 * r + 1]); gu[1][r] = pack_bf16(acc1[1][2 * r], acc1[1][2 * r + 1]); }
        }
        #pragma unroll
        for (int r = 0; r < 80; r++) acc[r] = 0.f;
        uint4* dst = reinterpret_cast<uint4*>(p.hT + ROWOFF((unit_of(role, t) - 10) * 64, rl, mb1 * 128 + (c.lane & 3) * 8));
        if (c.elect) TL(20 + c.wg);
        #pragma unroll
        for (int i = 0; i < 8; i++) {
          stage2_kb<false>(c, acc, i % R2, i / R2, (i + R2 - 1) % R2, i > 0, i);
          uint32_t w[4];
          #pragma unroll
          for (int b = 0; b < 4; b++) {
            const int r = 8 * (i & 3) + 2 * b + (i >> 2);
            w[b] = pack_bf16(silu_mul(bf_lo(gu[0][r]), bf_lo(gu[1][r])), silu_mul(bf_hi(gu[0][r]), bf_hi(gu[1][r])));
          }
          ST_H(dst, (i >> 2), (i & 3)) make_uint4(w[0], w[1], w[2], w[3]);
        }
        publish(c, t);
        wgmma_wait<0>();
        fence_acc(acc);
        i0 = 8;
      }
      if (i0 == 0) {
        #pragma unroll
        for (int r = 0; r < 80; r++) acc[r] = 0.f;
        named_sync(1 + c.wg, 256);
        if (c.elect) TL(20 + c.wg);
      }
      int slot = i0 % R2, ph = i0 / R2, prev = (i0 + R2 - 1) % R2;
      #pragma unroll 1
      for (int i = i0; i < nC; i++) {
        stage2_kb<false>(c, acc, slot, ph, prev, i > 0, i);
        prev = slot;
        if (++slot == R2) { slot = 0; ph ^= 1; }
      }
      if (c.elect) TL(22 + c.wg);
      #pragma unroll 1
      for (int i = nC; i < n2; i++) {
        if (STAG > 0 && i == n2 - STAG && c.wg != EARLYWG) {
          wgmma_wait<0>();
          if (STAG == R2) release2(c, prev);
          named_sync(4, 256);
        }
        if (EARLY_ARV && i == n2 - 1 && c.wg == EARLYWG) named_arrive(4, 256);
        stage2_kb<true>(c, acc, slot, ph, prev, i - 1 < n2 - R2 && !(STAG == R2 && c.wg != EARLYWG && i == n2 - STAG), i);
        prev = slot;
        if (++slot == R2) { slot = 0; ph ^= 1; }
      }
      if (!EARLY_ARV && STAG > 0 && c.wg == EARLYWG) named_arrive(4, 256);
      wgmma_wait<0>();
      fence_acc(acc);
      if (c.elect) { TL(24 + c.wg); T2(64 + c.wg * 64 + n2); }
      stage2_finish(acc, o, xr, c.wg == EARLYWG);

      if (c.elect) { TL(28 + c.wg); T2(64 + c.wg * 64 + n2 + 1); }
    }
  }
}

typedef CUresult (*PFN_encodeTiled)(CUtensorMap*, CUtensorMapDataType, cuuint32_t, void*, const cuuint64_t*, const cuuint64_t*,
                                    const cuuint32_t*, const cuuint32_t*, CUtensorMapInterleave, CUtensorMapSwizzle,
                                    CUtensorMapL2promotion, CUtensorMapFloatOOBfill);

void make_map(PFN_encodeTiled enc, CUtensorMap* m, const void* ptr, uint64_t rows, uint64_t cols, uint32_t box_rows, uint32_t box_cols, CUtensorMapSwizzle sw) {
  cuuint64_t dims[2] = {cols, rows};
  cuuint64_t strides[1] = {cols * 2};
  cuuint32_t box[2] = {box_cols, box_rows};
  cuuint32_t es[2] = {1, 1};
  enc(m, CU_TENSOR_MAP_DATA_TYPE_BFLOAT16, 2, const_cast<void*>(ptr), dims, strides, box, es, CU_TENSOR_MAP_INTERLEAVE_NONE, sw,
      CU_TENSOR_MAP_L2_PROMOTION_L2_256B, CU_TENSOR_MAP_FLOAT_OOB_FILL_NONE);
}
void make_map3(PFN_encodeTiled enc, CUtensorMap* m, const void* ptr, uint64_t rows, uint64_t cols, uint32_t box_rows, uint32_t box_cols, uint32_t nblk, CUtensorMapSwizzle sw) {
  cuuint64_t dims[3] = {box_cols, rows, cols / box_cols};
  cuuint64_t strides[2] = {cols * 2, (cuuint64_t)box_cols * 2};
  cuuint32_t box[3] = {box_cols, box_rows, nblk};
  cuuint32_t es[3] = {1, 1, 1};
  enc(m, CU_TENSOR_MAP_DATA_TYPE_BFLOAT16, 3, const_cast<void*>(ptr), dims, strides, box, es, CU_TENSOR_MAP_INTERLEAVE_NONE, sw,
      CU_TENSOR_MAP_L2_PROMOTION_L2_256B, CU_TENSOR_MAP_FLOAT_OOB_FILL_NONE);
}

}

extern "C" void kernel_launch(void* const* d_in, const int* in_sizes, int n_in, void* d_out, int out_size) {
  (void)in_sizes; (void)n_in; (void)out_size;
  PFN_encodeTiled enc = nullptr;
  cudaDriverEntryPointQueryResult qres;
  cudaGetDriverEntryPoint("cuTensorMapEncodeTiled", (void**)&enc, cudaEnableDefault, &qres);
  Params p;
  p.x = (const __nv_bfloat16*)d_in[0]; p.out = (__nv_bfloat16*)d_out;
  cudaGetSymbolAddress((void**)&p.xn, g_xn); cudaGetSymbolAddress((void**)&p.cnt, g_cnt);
  cudaGetSymbolAddress((void**)&p.abT, g_abT); cudaGetSymbolAddress((void**)&p.hT, g_hT);
  p.cr = (const __nv_bfloat16*)d_in[1]; p.ci = (const __nv_bfloat16*)d_in[2];
  p.dr = (const __nv_bfloat16*)d_in[3]; p.di = (const __nv_bfloat16*)d_in[4];
  p.wg = (const __nv_bfloat16*)d_in[6]; p.wu = (const __nv_bfloat16*)d_in[7]; p.wd = (const __nv_bfloat16*)d_in[8];
  Maps maps;
  make_map(enc, &maps.xn, p.xn, S_, D_, 128, 64, CU_TENSOR_MAP_SWIZZLE_128B);
  make_map(enc, &maps.dr, d_in[3], D_, D_, 128, 64, CU_TENSOR_MAP_SWIZZLE_128B);
  make_map(enc, &maps.di, d_in[4], D_, D_, 128, 64, CU_TENSOR_MAP_SWIZZLE_128B);
  make_map(enc, &maps.wg, d_in[6], D_, F_, 64, 64, CU_TENSOR_MAP_SWIZZLE_128B);
  make_map(enc, &maps.wu, d_in[7], D_, F_, 64, 64, CU_TENSOR_MAP_SWIZZLE_128B);
  make_map(enc, &maps.cr, d_in[1], S_, S_, 128, 64, CU_TENSOR_MAP_SWIZZLE_128B);
  make_map(enc, &maps.ci, d_in[2], S_, S_, 128, 64, CU_TENSOR_MAP_SWIZZLE_128B);
  make_map3(enc, &maps.h, p.hT, F_, S_, 64, 64, 2, CU_TENSOR_MAP_SWIZZLE_128B);
  make_map(enc, &maps.ab, p.abT, 2 * D_, S_, 80, 64, CU_TENSOR_MAP_SWIZZLE_128B);
  make_map3(enc, &maps.wd, d_in[8], F_, D_, 32, 32, 5, CU_TENSOR_MAP_SWIZZLE_64B);
  cudaFuncSetAttribute(fused_kernel, cudaFuncAttributeMaxDynamicSharedMemorySize, SMEM_BYTES);
  cudaLaunchConfig_t cfg = {};
  cfg.gridDim = dim3(NUM_CTAS); cfg.blockDim = dim3(384); cfg.dynamicSmemBytes = SMEM_BYTES; cfg.stream = cudaStreamPerThread;
  cudaLaunchAttribute at[1];
  at[0].id = cudaLaunchAttributeClusterDimension; at[0].val.clusterDim.x = 2; at[0].val.clusterDim.y = 1; at[0].val.clusterDim.z = 1;
  cfg.attrs = at; cfg.numAttrs = 1;
  cudaLaunchKernelEx(&cfg, fused_kernel, p, maps);
}
```

```cpp
#include <cuda_runtime.h>
#include <cuda_bf16.h>
#include <cuda.h>
#include <stdint.h>

template<int TA, int TB, int SA> __device__ __forceinline__ void wgmma_ss_n128(float (&d)[64], uint64_t da, uint64_t db, int sd) {
  asm volatile("{\n.reg .pred p;\nsetp.ne.b32 p, %66, 0;\n"
    "wgmma.mma_async.sync.aligned.m64n128k16.f32.bf16.bf16 {%0, %1, %2, %3, %4, %5, %6, %7, %8, %9, %10, %11, %12, %13, %14, %15, %16, %17, %18, %19, %20, %21, %22, %23, %24, %25, %26, %27, %28, %29, %30, %31, %32, %33, %34, %35, %36, %37, %38, %39, %40, %41, %42, %43, %44, %45, %46, %47, %48, %49, %50, %51, %52, %53, %54, %55, %56, %57, %58, %59, %60, %61, %62, %63}, %64, %65, p, %69, 1, %67, %68;\n}\n"
    : "+f"(d[0]), "+f"(d[1]), "+f"(d[2]), "+f"(d[3]), "+f"(d[4]), "+f"(d[5]), "+f"(d[6]), "+f"(d[7]), "+f"(d[8]), "+f"(d[9]), "+f"(d[10]), "+f"(d[11]), "+f"(d[12]), "+f"(d[13]), "+f"(d[14]), "+f"(d[15]), "+f"(d[16]), "+f"(d[17]), "+f"(d[18]), "+f"(d[19]), "+f"(d[20]), "+f"(d[21]), "+f"(d[22]), "+f"(d[23]), "+f"(d[24]), "+f"(d[25]), "+f"(d[26]), "+f"(d[27]), "+f"(d[28]), "+f"(d[29]), "+f"(d[30]), "+f"(d[31]), "+f"(d[32]), "+f"(d[33]), "+f"(d[34]), "+f"(d[35]), "+f"(d[36]), "+f"(d[37]), "+f"(d[38]), "+f"(d[39]), "+f"(d[40]), "+f"(d[41]), "+f"(d[42]), "+f"(d[43]), "+f"(d[44]), "+f"(d[45]), "+f"(d[46]), "+f"(d[47]), "+f"(d[48]), "+f"(d[49]), "+f"(d[50]), "+f"(d[51]), "+f"(d[52]), "+f"(d[53]), "+f"(d[54]), "+f"(d[55]), "+f"(d[56]), "+f"(d[57]), "+f"(d[58]), "+f"(d[59]), "+f"(d[60]), "+f"(d[61]), "+f"(d[62]), "+f"(d[63])
    : "l"(da), "l"(db), "r"(sd), "n"(TA), "n"(TB), "n"(SA));
}
template<int TA, int TB, int SA> __device__ __forceinline__ void wgmma_ss_n160(float (&d)[80], uint64_t da, uint64_t db, int sd) {
  asm volatile("{\n.reg .pred p;\nsetp.ne.b32 p, %82, 0;\n"
    "wgmma.mma_async.sync.aligned.m64n160k16.f32.bf16.bf16 {%0, %1, %2, %3, %4, %5, %6, %7, %8, %9, %10, %11, %12, %13, %14, %15, %16, %17, %18, %19, %20, %21, %22, %23, %24, %25, %26, %27, %28, %29, %30, %31, %32, %33, %34, %35, %36, %37, %38, %39, %40, %41, %42, %43, %44, %45, %46, %47, %48, %49, %50, %51, %52, %53, %54, %55, %56, %57, %58, %59, %60, %61, %62, %63, %64, %65, %66, %67, %68, %69, %70, %71, %72, %73, %74, %75, %76, %77, %78, %79}, %80, %81, p, %85, 1, %83, %84;\n}\n"
    : "+f"(d[0]), "+f"(d[1]), "+f"(d[2]), "+f"(d[3]), "+f"(d[4]), "+f"(d[5]), "+f"(d[6]), "+f"(d[7]), "+f"(d[8]), "+f"(d[9]), "+f"(d[10]), "+f"(d[11]), "+f"(d[12]), "+f"(d[13]), "+f"(d[14]), "+f"(d[15]), "+f"(d[16]), "+f"(d[17]), "+f"(d[18]), "+f"(d[19]), "+f"(d[20]), "+f"(d[21]), "+f"(d[22]), "+f"(d[23]), "+f"(d[24]), "+f"(d[25]), "+f"(d[26]), "+f"(d[27]), "+f"(d[28]), "+f"(d[29]), "+f"(d[30]), "+f"(d[31]), "+f"(d[32]), "+f"(d[33]), "+f"(d[34]), "+f"(d[35]), "+f"(d[36]), "+f"(d[37]), "+f"(d[38]), "+f"(d[39]), "+f"(d[40]), "+f"(d[41]), "+f"(d[42]), "+f"(d[43]), "+f"(d[44]), "+f"(d[45]), "+f"(d[46]), "+f"(d[47]), "+f"(d[48]), "+f"(d[49]), "+f"(d[50]), "+f"(d[51]), "+f"(d[52]), "+f"(d[53]), "+f"(d[54]), "+f"(d[55]), "+f"(d[56]), "+f"(d[57]), "+f"(d[58]), "+f"(d[59]), "+f"(d[60]), "+f"(d[61]), "+f"(d[62]), "+f"(d[63]), "+f"(d[64]), "+f"(d[65]), "+f"(d[66]), "+f"(d[67]), "+f"(d[68]), "+f"(d[69]), "+f"(d[70]), "+f"(d[71]), "+f"(d[72]), "+f"(d[73]), "+f"(d[74]), "+f"(d[75]), "+f"(d[76]), "+f"(d[77]), "+f"(d[78]), "+f"(d[79])
    : "l"(da), "l"(db), "r"(sd), "n"(TA), "n"(TB), "n"(SA));
}

namespace {

constexpr int S_ = 2048, D_ = 640, F_ = 1728;
constexpr int A_CHUNK   = 16384;
constexpr int RING1_OFF = 10 * A_CHUNK;
constexpr int R1        = 4;
constexpr int SLOT2     = 36864;
constexpr int R2        = 6;
constexpr int BAR_OFF   = RING1_OFF + R1 * 16384;
constexpr int TAB_OFF   = BAR_OFF + 512;
constexpr int TL_OFF    = TAB_OFF + 1536;
constexpr int TL2_OFF = TL_OFF;
constexpr int SMEM_BYTES = TL_OFF + 1024;
constexpr int NUM_CTAS  = 132;
#define NC1 38
#define ND1 13
#define MAPV 1
#define REL1 0
#define REL2 0
#define FREE0 3
#define ZERO_NS 3500
#define PFKB 7
#define STAG 6
#define EARLYWG kh
#define XAHEAD 2
#define XW 1
#define PFW 0
#define KHA 1
#define EXP_ST 0
#define EXP_NOX 0
#define PACE_AB 70
#define PACE_H 0
#define PACE_Z 50
#define XEARLY 1
#define HLOOP 1
#define EXP_TAIL 0
#define CPF 0
#define CPF_START 2000
#define CPF_KH0 3000
#define CPF_GAP 800
#define CPF_FIRST 0
#define RPF 0
#define SILU_ORD 0
#define EARLY_ARV 0
#define UNI 2
#define XNAHEAD 2
#define PACE_RAW 0
#define PACE_LN 0
#define DPF 1
#define LDLATE 0
#define LDNS 200
#define ONEF 1
#define PFNS 1000
#define EXP_NRELOAD 5
#define ZDELAY 0
#define DFIRST 4
#define DDELAY 0
#define PF 0

__device__ __nv_bfloat16 g_xn[S_ * D_];
__device__ unsigned long long g_ll[S_ + 1024];
__device__ __nv_bfloat16 g_abT[2 * D_ * S_];
__device__ __nv_bfloat16 g_hT[F_ * S_];
constexpr int CNT_XN = 0, CNT_H = 16, CNT_HX = 32, CNT_A = 48, CNT_B = 49, CNT_DONE = 50, CNT_TOTAL = 51, CNT_EPOCH = 51;
__device__ unsigned g_cnt[(CNT_TOTAL + 1) * 32];
#define T2(idx) do {} while (0)
#define TL(idx) do {} while (0)

struct Params {
  const __nv_bfloat16* x; __nv_bfloat16* out;
  __nv_bfloat16* xn; unsigned long long* ll; unsigned* cnt; __nv_bfloat16* abT; __nv_bfloat16* hT;
  const __nv_bfloat16 *dr, *di, *wg, *wu, *wd, *cr, *ci;
};
struct Maps {
  CUtensorMap x, xn, dr, di, wg, wu, cr, ci, h, ab, wd;
};

__device__ __forceinline__ uint32_t smem_u32(const void* p) { return (uint32_t)__cvta_generic_to_shared(p); }
__device__ __forceinline__ void mbar_init(uint32_t bar, uint32_t count) { asm volatile("mbarrier.init.shared::cta.b64 [%0], %1;" :: "r"(bar), "r"(count)); }
__device__ __forceinline__ void mbar_expect_tx(uint32_t bar, uint32_t bytes) { asm volatile("mbarrier.arrive.expect_tx.shared::cta.b64 _, [%0], %1;" :: "r"(bar), "r"(bytes) : "memory"); }
__device__ __forceinline__ void mbar_arrive(uint32_t bar) { asm volatile("mbarrier.arrive.shared::cta.b64 _, [%0];" :: "r"(bar) : "memory"); }
__device__ __forceinline__ void mbar_arrive_cta(uint32_t bar, uint32_t cta) {
  asm volatile("{\n.reg .b32 ra;\nmapa.shared::cluster.u32 ra, %0, %1;\nmbarrier.arrive.shared::cluster.b64 _, [ra];\n}\n" :: "r"(bar), "r"(cta) : "memory");
}
__device__ __forceinline__ void mbar_arrive_if(uint32_t bar, uint32_t pred) {
  asm volatile("{\n.reg .pred p;\nsetp.ne.u32 p, %1, 0;\n@p mbarrier.arrive.shared::cta.b64 _, [%0];\n}\n" :: "r"(bar), "r"(pred) : "memory");
}
__device__ __forceinline__ void mbar_arrive_cta_if(uint32_t bar, uint32_t cta, uint32_t pred) {
  asm volatile("{\n.reg .pred p;\n.reg .b32 ra;\nsetp.ne.u32 p, %2, 0;\nmapa.shared::cluster.u32 ra, %0, %1;\n@p mbarrier.arrive.shared::cluster.b64 _, [ra];\n}\n" :: "r"(bar), "r"(cta), "r"(pred) : "memory");
}
__device__ __forceinline__ void mbar_wait(uint32_t bar, uint32_t parity) {
  asm volatile("{\n.reg .pred p;\n.reg .u32 n;\nmov.u32 n, 0;\n"
    "LAB_WAIT:\n"
    "mbarrier.try_wait.parity.shared::cta.b64 p, [%0], %1;\n"
    "@p bra LAB_DONE;\n"
    "add.u32 n, n, 1;\n"
    "setp.lt.u32 p, n, 4000000;\n"
    "@p bra LAB_WAIT;\n"
    "trap;\n"
    "LAB_DONE:\n}\n" :: "r"(bar), "r"(parity) : "memory");
}
__device__ __forceinline__ void tma_load(uint32_t dst, const CUtensorMap* map, int c0, int c1, uint32_t bar) {
  asm volatile("cp.async.bulk.tensor.2d.shared::cluster.global.mbarrier::complete_tx::bytes [%0], [%1, {%3, %4}], [%2];"
    :: "r"(dst), "l"(map), "r"(bar), "r"(c0), "r"(c1) : "memory");
}
__device__ __forceinline__ void tma_load_mc(uint32_t dst, const CUtensorMap* map, int c0, int c1, uint32_t bar) {
  asm volatile("cp.async.bulk.tensor.2d.shared::cluster.global.mbarrier::complete_tx::bytes.multicast::cluster [%0], [%1, {%3, %4}], [%2], %5;"
    :: "r"(dst), "l"(map), "r"(bar), "r"(c0), "r"(c1), "h"((uint16_t)3) : "memory");
}
__device__ __forceinline__ void tma_load_3d(uint32_t dst, const CUtensorMap* map, int c1, int c2, uint32_t bar) {
  asm volatile("cp.async.bulk.tensor.3d.shared::cluster.global.mbarrier::complete_tx::bytes [%0], [%1, {%5, %3, %4}], [%2];"
    :: "r"(dst), "l"(map), "r"(bar), "r"(c1), "r"(c2), "r"(0) : "memory");
}
__device__ __forceinline__ void tma_load_3d_mc(uint32_t dst, const CUtensorMap* map, int c1, int c2, uint32_t bar) {
  asm volatile("cp.async.bulk.tensor.3d.shared::cluster.global.mbarrier::complete_tx::bytes.multicast::cluster [%0], [%1, {%5, %3, %4}], [%2], %6;"
    :: "r"(dst), "l"(map), "r"(bar), "r"(c1), "r"(c2), "r"(0), "h"((uint16_t)3) : "memory");
}
__device__ __forceinline__ void tma_load_5d(uint32_t dst, const CUtensorMap* map, int c0, int c4, uint32_t bar) {
  asm volatile("cp.async.bulk.tensor.5d.shared::cluster.global.mbarrier::complete_tx::bytes [%0], [%1, {%3, %5, %5, %5, %4}], [%2];"
    :: "r"(dst), "l"(map), "r"(bar), "r"(c0), "r"(c4), "r"(0) : "memory");
}
__device__ __forceinline__ void tma_load_5d_mc(uint32_t dst, const CUtensorMap* map, int c0, int c4, uint32_t bar) {
  asm volatile("cp.async.bulk.tensor.5d.shared::cluster.global.mbarrier::complete_tx::bytes.multicast::cluster [%0], [%1, {%3, %5, %5, %5, %4}], [%2], %6;"
    :: "r"(dst), "l"(map), "r"(bar), "r"(c0), "r"(c4), "r"(0), "h"((uint16_t)3) : "memory");
}
__device__ __forceinline__ float4 lds_f4(uint32_t a) {
  float4 v; asm volatile("ld.shared.v4.f32 {%0,%1,%2,%3}, [%4];" : "=f"(v.x), "=f"(v.y), "=f"(v.z), "=f"(v.w) : "r"(a) : "memory"); return v;
}
__device__ __forceinline__ void tma_prefetch(const CUtensorMap* map, int c0, int c1) {
  asm volatile("cp.async.bulk.prefetch.tensor.2d.L2.global [%0, {%1, %2}];" :: "l"(map), "r"(c0), "r"(c1) : "memory");
}
__device__ __forceinline__ void prefetch_map(const CUtensorMap* map) { asm volatile("prefetch.tensormap [%0];" :: "l"(map) : "memory"); }
__device__ __forceinline__ void l2_prefetch(const void* p, uint32_t bytes) { asm volatile("cp.async.bulk.prefetch.L2.global [%0], %1;" :: "l"(p), "r"(bytes) : "memory"); }
__device__ __forceinline__ void wgmma_fence() { asm volatile("wgmma.fence.sync.aligned;" ::: "memory"); }
__device__ __forceinline__ void wgmma_commit() { asm volatile("wgmma.commit_group.sync.aligned;" ::: "memory"); }
template<int N> __device__ __forceinline__ void wgmma_wait() { asm volatile("wgmma.wait_group.sync.aligned %0;" :: "n"(N) : "memory"); }
template<int N> __device__ __forceinline__ void fence_acc(float (&d)[N]) {
  #pragma unroll
  for (int i = 0; i < N; i++) asm volatile("" : "+f"(d[i]) :: "memory");
}
__device__ __forceinline__ void named_sync(int id, int n) { asm volatile("bar.sync %0, %1;" :: "r"(id), "r"(n) : "memory"); }
__device__ __forceinline__ void named_arrive(int id, int n) { asm volatile("bar.arrive %0, %1;" :: "r"(id), "r"(n) : "memory"); }
template<int R> __device__ __forceinline__ void reg_alloc() { asm volatile("setmaxnreg.inc.sync.aligned.u32 %0;" :: "n"(R)); }
template<int R> __device__ __forceinline__ void reg_dealloc() { asm volatile("setmaxnreg.dec.sync.aligned.u32 %0;" :: "n"(R)); }
__device__ __forceinline__ void fence_proxy_async_global() { asm volatile("fence.proxy.async.global;" ::: "memory"); }
#define WFENCE fence_proxy_async_global()
#define PFENCE fence_proxy_async_global()
template<int NS> __device__ __forceinline__ void pace() { if (NS > 0) asm volatile("nanosleep.u32 %0;" :: "n"(NS) : "memory"); }
__device__ __forceinline__ void red_release(unsigned* p) { asm volatile("red.release.gpu.global.add.u32 [%0], 1;" :: "l"(p) : "memory"); }
__device__ __forceinline__ void red_relaxed(unsigned* p) { asm volatile("red.relaxed.gpu.global.add.u32 [%0], 1;" :: "l"(p) : "memory"); }
#define PUB_RED red_release
__device__ __forceinline__ unsigned ld_relaxed(const unsigned* p) { unsigned v; asm volatile("ld.relaxed.gpu.global.u32 %0, [%1];" : "=r"(v) : "l"(p) : "memory"); return v; }
__device__ __forceinline__ void ll_store(unsigned long long* p, uint32_t v, uint32_t epoch) {
  asm volatile("{\n.reg .b64 w;\n.reg .u32 t;\nadd.u32 t, %2, 1;\nmov.b64 w, {%1, t};\nst.relaxed.gpu.global.b64 [%0], w;\n}\n" :: "l"(p), "r"(v), "r"(epoch) : "memory");
}
__device__ __forceinline__ uint4 ll_load4(const unsigned long long* p, uint32_t tag) {
  uint4 v;
  asm volatile("{\n.reg .pred p;\n.reg .u32 n, t0, t1, t2, t3;\n.reg .b64 w0, w1, w2, w3;\nmov.u32 n, 0;\n"
    "LAB_WAIT:\n"
    "ld.relaxed.gpu.global.v2.b64 {w0, w1}, [%4];\n"
    "ld.relaxed.gpu.global.v2.b64 {w2, w3}, [%4 + 16];\n"
    "mov.b64 {%0, t0}, w0;\nmov.b64 {%1, t1}, w1;\nmov.b64 {%2, t2}, w2;\nmov.b64 {%3, t3}, w3;\n"
    "xor.b32 t0, t0, %5;\nxor.b32 t1, t1, %5;\nxor.b32 t2, t2, %5;\nxor.b32 t3, t3, %5;\n"
    "or.b32 t0, t0, t1;\nor.b32 t2, t2, t3;\nor.b32 t0, t0, t2;\n"
    "setp.eq.u32 p, t0, 0;\n"
    "@p bra LAB_DONE;\n"
    "nanosleep.u32 100;\n"
    "add.u32 n, n, 1;\n"
    "setp.lt.u32 p, n, 2000000;\n"
    "@p bra LAB_WAIT;\n"
    "trap;\n"
    "LAB_DONE:\n}\n" : "=r"(v.x), "=r"(v.y), "=r"(v.z), "=r"(v.w) : "l"(p), "r"(tag) : "memory");
  return v;
}
__device__ __forceinline__ float rcp_approx(float x) { float r; asm("rcp.approx.f32 %0, %1;" : "=f"(r) : "f"(x)); return r; }
template<int SLEEP_NS>
__device__ __forceinline__ void wait_counter(const unsigned* p, unsigned target) {
  asm volatile("{\n.reg .pred p;\n.reg .u32 n, v;\nmov.u32 n, 0;\n"
    "LAB_WAIT:\n"
    "ld.acquire.gpu.global.u32 v, [%0];\n"
    "setp.ge.u32 p, v, %1;\n"
    "@p bra LAB_DONE;\n"
    "nanosleep.u32 %2;\n"
    "add.u32 n, n, 1;\n"
    "setp.lt.u32 p, n, 2000000;\n"
    "@p bra LAB_WAIT;\n"
    "trap;\n"
    "LAB_DONE:\n}\n" :: "l"(p), "r"(target), "n"(SLEEP_NS) : "memory");
}
constexpr uint32_t HI_SW128 = (1024 >> 4) | (1u << 30);
constexpr uint32_t HI_SW64  = (512 >> 4) | (2u << 30);
constexpr uint32_t DBASE    = 0x400 >> 4;
constexpr uint32_t LBO_NONE = 1u << 16;
constexpr uint32_t LBO_2K   = (2048u >> 4) << 16;
__device__ __forceinline__ uint64_t mk_desc(uint32_t lo, uint32_t hi) { uint64_t d; asm("mov.b64 %0, {%1, %2};" : "=l"(d) : "r"(lo), "r"(hi)); return d; }

__device__ __forceinline__ uint32_t pack_bf16(float lo, float hi) {
  uint32_t r; asm("cvt.rn.bf16x2.f32 %0, %1, %2;" : "=r"(r) : "f"(hi), "f"(lo)); return r;
}
__device__ __forceinline__ float bf_lo(uint32_t v) { return __uint_as_float(v << 16); }
__device__ __forceinline__ float bf_hi(uint32_t v) { return __uint_as_float(v & 0xffff0000u); }
__device__ __forceinline__ float round_bf(float v) { return bf_lo(pack_bf16(v, 0.f)); }
__device__ __forceinline__ uint32_t norm2(uint32_t x, uint32_t m2, uint32_t ih2, uint32_t il2) {
  uint32_t d, t, r;
  asm("sub.rn.bf16x2 %0, %1, %2;" : "=r"(d) : "r"(x), "r"(m2));
  asm("mul.rn.bf16x2 %0, %1, %2;" : "=r"(t) : "r"(d), "r"(il2));
  asm("fma.rn.bf16x2 %0, %1, %2, %3;" : "=r"(r) : "r"(d), "r"(ih2), "r"(t));
  return r;
}
__device__ __forceinline__ float sum8(const uint4& v) {
  return ((bf_lo(v.x) + bf_hi(v.x)) + (bf_lo(v.y) + bf_hi(v.y))) + ((bf_lo(v.z) + bf_hi(v.z)) + (bf_lo(v.w) + bf_hi(v.w)));
}
__device__ __forceinline__ float silu_mul(float g, float u, float nl2e = -1.4426950408889634f) {
  float e, r;
  asm("ex2.approx.ftz.f32 %0, %1;" : "=f"(e) : "f"(g * nl2e));
  asm("rcp.approx.ftz.f32 %0, %1;" : "=f"(r) : "f"(e + 1.0f));
  return (g * u) * r;
}
__device__ __forceinline__ int xn_row(int t) { return (t & ~30) | ((t & 6) << 2) | ((t & 24) >> 2); }
__device__ __forceinline__ int unit_of(int role, int t) {
  const int two_ab = (role & 5) == 0;
  if (t == 0) return role;
  if (t == 1 && two_ab) return 8 + (role >> 1);
  return 9 + 3 * role + (role > 4) + (role > 6) + t - two_ab;
}

struct UnitSrc { const CUtensorMap *m0, *m1; int x0, y0, y1, dx, dy; };
__device__ __forceinline__ UnitSrc unit_src(const Maps& maps, int unit) {
  UnitSrc u;
  const bool ab = unit < 10;
  u.m0 = &maps.dr + (ab ? (unit >= 5) : 2);
  u.m1 = u.m0 + (ab ? 0 : 1);
  u.x0 = ab ? 0 : (unit - 10) * 64;
  u.y0 = ab ? (unit - (unit >= 5) * 5) * 128 : 0;
  u.y1 = u.y0 + (ab ? 64 : 0);
  u.dx = ab ? 64 : 0; u.dy = 64 - u.dx;
  return u;
}
__device__ __forceinline__ void prefetch_unit(const Maps& maps, int unit, int kb) {
  const UnitSrc u = unit_src(maps, unit);
  tma_prefetch(u.m0, u.x0 + kb * u.dx, u.y0 + kb * u.dy);
  tma_prefetch(u.m1, u.x0 + kb * u.dx, u.y1 + kb * u.dy);
}

struct Ctx {
  uint32_t sbase, full1, empty1, full2, empty2, flagb, pub, xfull, xfree;
  int wg, warp, lane, zero;
  bool elect;
};

template<int MODE, bool LAST, bool RAW>
__device__ __forceinline__ void stage1_mma(const Ctx& c, float (&acc)[2][64], int it0, bool wait_xn, bool has_next, bool free_all) {
  int prev = 0;
  #pragma unroll 1
  for (int kb = 0; kb < 10; kb++) {
    const int it = it0 + kb;
    const int slot = it & 3;
    const uint32_t bx = DBASE + kb * (A_CHUNK >> 4) + LBO_NONE;
    const uint32_t ar = DBASE + slot * 1024 + ((RING1_OFF >> 4) + LBO_NONE);
    const uint32_t rel = c.elect && kb > 0, rel2 = c.elect && kb >= 3 && (kb & 1);
    if (RAW) mbar_wait(c.xfull + 8 * kb, 0);
    else if (!LAST && wait_xn) mbar_wait(c.xfull + 8 * kb, 1);
    mbar_wait(c.full1 + 8 * slot, (it >> 2) & 1);
    if (kb == 9 && has_next) named_arrive(1 + (c.wg ^ 1), 256);
    wgmma_fence();
    #pragma unroll
    for (int k = 0; k < 4; k++) {
      #pragma unroll
      for (int i = 0; i < 2; i++) {
        if (MODE == 2) wgmma_ss_n128<1, 0, 1>(acc[i], mk_desc(ar + i * 512 + k * 128, HI_SW128), mk_desc(bx + k * 2, HI_SW128), (kb | k) != 0);
        else           wgmma_ss_n128<0, 0, (MODE == 1 ? -1 : 1)>(acc[i], mk_desc(ar + i * 512 + k * 2, HI_SW128), mk_desc(bx + k * 2, HI_SW128), (kb | k) != 0);
      }
      if (k == 0) {
        wgmma_commit();
        wgmma_wait<1>();
        if (c.elect) T2(it + it0 / 10);
        mbar_arrive_if(c.empty1 + 8 * prev, rel);
        wgmma_fence();
      }
      if (LAST && (k == 1 || k == 2)) mbar_arrive_cta_if(c.empty2 + 4 * (kb - 3), k - 1, rel2);
      if (RAW && k == 1) mbar_arrive_cta_if(c.xfree + 8 * (kb - 1), (kb - 1) & 1, rel);
    }
    wgmma_commit();
    prev = slot;
  }
  #pragma unroll 1
  for (int z = c.zero; z < 1; z++) {
    wgmma_wait<0>();
    if (c.elect) {
      mbar_arrive(c.empty1 + 8 * prev);
      if (RAW) mbar_arrive_cta(c.xfree + 8 * 9, 1);
      TL(33 + (it0 / 10) * 4); T2(it0 + 10 + it0 / 10);
      if (LAST || free_all) {
        #pragma unroll
        for (int j = LAST ? 4 : 0; j < R2; j++) { mbar_arrive_cta(c.empty2 + 8 * j, 0); mbar_arrive_cta(c.empty2 + 8 * j, 1); }
      }
    }
  }
  wgmma_wait<0>();
  fence_acc(acc[0]); fence_acc(acc[1]);
}
#define ST_AB(dst, i, hf, J) if (EXP_ST == 0 || acc[0][0] == 1.2345f) dst[((i) * 64 + (hf) * 8) * (S_ / 8) + (J) * 4] =
#define ST_H(dst, hf, J) if (EXP_ST == 0 || w[0] == 0x12345) dst[(hf) * 8 * (S_ / 8) + (J) * 4] =
#define ROWOFF(u, rl, col) ((size_t)((u) + (rl)) * S_ + (col))
__device__ __forceinline__ void store_ab(const float (&acc)[2][64], uint4* dst) {
  #pragma unroll
  for (int i = 0; i < 2; i++)
    #pragma unroll
    for (int hf = 0; hf < 2; hf++)
      #pragma unroll
      for (int J = 0; J < 4; J++) {
        const int r = 16 * J + 2 * hf;
        ST_AB(dst, i, hf, J) make_uint4(pack_bf16(acc[i][r], acc[i][r + 1]), pack_bf16(acc[i][r + 4], acc[i][r + 5]),
                                                               pack_bf16(acc[i][r + 8], acc[i][r + 9]), pack_bf16(acc[i][r + 12], acc[i][r + 13]));
        if (i + hf + J < 5) pace<PACE_AB>();
      }
}
__device__ __forceinline__ void store_ab_raw(const Ctx& c, const float (&acc)[2][64], uint4* dst, int rl, float sgn) {
  const uint32_t st = c.sbase + TAB_OFF + (c.lane & 3) * 32;
  float sm[2][2];
  #pragma unroll
  for (int i = 0; i < 2; i++)
    #pragma unroll
    for (int hf = 0; hf < 2; hf++) {
      asm volatile("ld.shared.f32 %0, [%1];" : "=f"(sm[i][hf]) : "r"(c.sbase + TAB_OFF + 1024 + (i * 64 + hf * 8 + rl) * 4) : "memory");
      sm[i][hf] *= sgn;
    }
  #pragma unroll
  for (int J = 0; J < 4; J++) {
    const float4 m0 = lds_f4(st + J * 128), m1 = lds_f4(st + J * 128 + 16), r0 = lds_f4(st + 512 + J * 128), r1 = lds_f4(st + 512 + J * 128 + 16);
    const float nm[8] = {m0.x, m0.y, m0.z, m0.w, m1.x, m1.y, m1.z, m1.w}, rs[8] = {r0.x, r0.y, r0.z, r0.w, r1.x, r1.y, r1.z, r1.w};
    #pragma unroll
    for (int i = 0; i < 2; i++)
      #pragma unroll
      for (int hf = 0; hf < 2; hf++) {
        #pragma unroll 1
        for (int z = c.zero; z < 1; z++) {
          const float s = sm[i][hf] + __int_as_float(z);
          uint32_t w[4];
          #pragma unroll
          for (int b = 0; b < 4; b++) {
            const int r = 16 * J + 4 * b + 2 * hf;
            w[b] = pack_bf16(fmaf(nm[2 * b], s, acc[i][r]) * rs[2 * b], fmaf(nm[2 * b + 1], s, acc[i][r + 1]) * rs[2 * b + 1]);
          }
          dst[(i * 64 + hf * 8) * (S_ / 8) + J * 4] = make_uint4(w[0], w[1], w[2], w[3]);
        }
        if (i + hf + J < 5) pace<PACE_RAW>();
      }
  }
}
__device__ __forceinline__ void store_h_slice(const float (&acc)[2][64], uint4* dst, int sl, float nl2e) {
  const int hf = sl >> 2, J = sl & 3;
  uint32_t w[4];
  #pragma unroll
  for (int b = 0; b < 4; b++) {
    const int r = 16 * J + 4 * b + 2 * hf;
    w[b] = pack_bf16(silu_mul(acc[0][r], acc[1][r], nl2e), silu_mul(acc[0][r + 1], acc[1][r + 1], nl2e));
  }
  ST_H(dst, hf, J) make_uint4(w[0], w[1], w[2], w[3]);
}
__device__ __forceinline__ void publish(const Ctx& c, int t) {
  if (c.elect) TL(34 + t * 4);
  __syncwarp();
  if (c.lane == 0) mbar_arrive(c.pub + 8 * t);
}
__device__ __forceinline__ void release2(const Ctx& c, int slot) {
  if (c.elect) { mbar_arrive_cta(c.empty2 + 8 * slot, 0); mbar_arrive_cta(c.empty2 + 8 * slot, 1); }
}
template<bool DPART>
__device__ __forceinline__ void stage2_kb(const Ctx& c, float (&acc)[80], int slot, int ph, int prev, bool rel, int ii) {
  const uint32_t sa = DBASE + slot * (SLOT2 >> 4) + c.wg * 512 + LBO_NONE, sb = DBASE + slot * (SLOT2 >> 4) + (1024 + (DPART ? LBO_2K : LBO_NONE));
  mbar_wait(c.full2 + 8 * slot, ph);
  wgmma_fence();
  #pragma unroll
  for (int k = 0; k < 4; k++) {
    if (DPART) wgmma_ss_n160<1, 1, 1>(acc, mk_desc(sa + k * 128, HI_SW128), mk_desc(sb + (k >> 1) * 640 + (k & 1) * 64, HI_SW64), 1);
    else       wgmma_ss_n160<0, 0, 1>(acc, mk_desc(sa + k * 2, HI_SW128), mk_desc(sb + k * 2, HI_SW128), 1);
    if (k == REL2) {
      wgmma_commit();
      wgmma_wait<1>();
      if (c.elect) T2(64 + c.wg * 64 + ii);
      if (rel) release2(c, prev);
      if (k < 3) wgmma_fence();
    }
  }
  if (REL2 < 3) wgmma_commit();
}

struct OutAddr { uint32_t sw, lf, lh; char *gf, *gh; };
__device__ __forceinline__ uint32_t add_bf2(uint32_t a, uint32_t b) { uint32_t r; asm("add.rn.bf16x2 %0, %1, %2;" : "=r"(r) : "r"(a), "r"(b)); return r; }
__device__ __forceinline__ void stage2_finish(const float (&acc)[80], const OutAddr& o, const uint4 (&xr)[10], bool add_x) {
  if (EXP_TAIL == 1 && add_x && acc[0] != 1.2345f) return;
  #pragma unroll
  for (int jj = 0; jj < 10; jj++) {
    asm volatile("stmatrix.sync.aligned.m8n8.x4.shared.b16 [%0], {%1, %2, %3, %4};" :: "r"(o.sw + jj * 32),
                 "r"(pack_bf16(acc[8 * jj], acc[8 * jj + 1])), "r"(pack_bf16(acc[8 * jj + 2], acc[8 * jj + 3])),
                 "r"(pack_bf16(acc[8 * jj + 4], acc[8 * jj + 5])), "r"(pack_bf16(acc[8 * jj + 6], acc[8 * jj + 7])) : "memory");
  }
  __syncwarp();
  if (EXP_TAIL == 2 && add_x && acc[0] != 1.2345f) return;
  uint4 v[10];
  #pragma unroll
  for (int i = 0; i < 10; i++) {
    const uint32_t a = i < 8 ? o.lf + (i >> 1) * (4 * 336) + (i & 1) * 128 : o.lh + (i - 8) * (8 * 336);
    asm volatile("ld.shared.v4.u32 {%0, %1, %2, %3}, [%4];" : "=r"(v[i].x), "=r"(v[i].y), "=r"(v[i].z), "=r"(v[i].w) : "r"(a) : "memory");
  }
  if (add_x) {
    #pragma unroll
    for (int i = 0; i < 10; i++) { v[i].x = add_bf2(v[i].x, xr[i].x); v[i].y = add_bf2(v[i].y, xr[i].y); v[i].z = add_bf2(v[i].z, xr[i].z); v[i].w = add_bf2(v[i].w, xr[i].w); }
  }
  if (EXP_TAIL == 3 && add_x && v[0].x != 0x12345) return;
  #pragma unroll
  for (int i = 0; i < 10; i++) {
    char* g = i < 8 ? o.gf + (i >> 1) * (4 * D_ * 2) + (i & 1) * 128 : o.gh + (i - 8) * (8 * D_ * 2);
    asm volatile("red.global.add.noftz.v4.bf16x2 [%0], {%1, %2, %3, %4};" :: "l"(g), "r"(v[i].x), "r"(v[i].y), "r"(v[i].z), "r"(v[i].w) : "memory");
  }
}

__global__ void __launch_bounds__(384, 1)
fused_kernel(const __grid_constant__ Params p, const __grid_constant__ Maps maps) {
  extern __shared__ __align__(1024) uint8_t smem_raw[];
  const int cl = blockIdx.x >> 1, rank = blockIdx.x & 1;
  const bool extra = cl >= 64;
  const int tok = (blockIdx.x & 127) * 16 + ((threadIdx.x >> 4) & 15), l16 = threadIdx.x & 15;
  uint4 v[5];
  uint32_t x0 = 0;
  if (threadIdx.x < 256) {
    const uint4* xs = reinterpret_cast<const uint4*>(p.x + (size_t)tok * D_);
    #pragma unroll
    for (int i = 0; i < 5; i++) v[i] = __ldg(xs + l16 + 16 * i);
    x0 = __ldg(reinterpret_cast<const uint32_t*>(xs));
  }
  uint32_t epoch = 0;
  if (threadIdx.x < 256) epoch = ld_relaxed(&p.cnt[CNT_EPOCH * 32]);
  int kh, nt, grp;
  {
    int pos, half;
    if (cl >= 4 && cl < 36) { half = 0; pos = (cl - 4) & 7; nt = (cl - 4) >> 3; }
    else if (cl >= 36)      { half = 1; nt = (cl - 36) / 7; pos = 1 + (cl - 36) - nt * 7; nt &= 3; }
    else                    { half = 1; pos = 0; nt = cl; }
    kh = (pos >> 2) ^ KHA ^ 1; grp = (pos & 3) * 2 + half;
  }
  const int mb2 = grp * 2 + rank;
  const int role = kh + 2 * ((nt & 1) * 2 + rank);
  const int mb1 = extra ? (cl - 64) * 8 + rank : grp * 2 + (nt >> 1);

  Ctx c;
  c.sbase = __shfl_sync(0xffffffffu, smem_u32(smem_raw), 0);
  c.zero = __shfl_sync(0xffffffffu, threadIdx.x >> 10, 0);
  c.full1 = c.sbase + BAR_OFF; c.empty1 = c.full1 + 8 * R1; c.full2 = c.empty1 + 8 * R1; c.empty2 = c.full2 + 8 * R2;
  c.flagb = c.empty2 + 8 * R2; c.pub = c.flagb + 8 * 6; c.xfull = c.pub + 8 * 5; c.xfree = c.xfull + 8 * 10;
  c.wg = __shfl_sync(0xffffffffu, threadIdx.x >> 7, 0);
  c.warp = __shfl_sync(0xffffffffu, (threadIdx.x >> 5) & 3, 0);
  c.lane = threadIdx.x & 31;
  c.elect = (threadIdx.x & 127) == 0;

  const int nT = extra ? 4 : 5 - kh;
  const int nC = kh ? NC1 : 64 - NC1, c0 = kh ? 0 : NC1, nD = kh ? ND1 : 27 - ND1, d0 = kh ? 0 : ND1;
  const int n2 = nC + nD;

  int wlo = c.warp & 1, whi = c.warp >> 1;
  asm volatile("" : "+r"(wlo)); asm volatile("" : "+r"(whi));
  const bool w0 = !whi && !wlo, w1 = !whi && wlo, w2 = whi && !wlo;
  if (c.wg == 2 && c.lane == 0) {
    if (w0) {
      #pragma unroll
      for (int i = 0; i < 2 * R1; i++) mbar_init(c.full1 + 8 * i, 1);
    } else if (w1) {
      #pragma unroll
      for (int i = 0; i < 10; i++) mbar_init(c.xfull + 8 * i, 1);
    } else if (w2) {
      #pragma unroll
      for (int i = 0; i < R2; i++) { mbar_init(c.full2 + 8 * i, 1); mbar_init(c.empty2 + 8 * i, 4); }
      #pragma unroll
      for (int i = 0; i < 5; i++) mbar_init(c.xfree + 8 * i, 2);
    } else {
      #pragma unroll
      for (int i = 0; i < 5; i++) mbar_init(c.flagb + 8 * i, 1);
      mbar_init(c.flagb + 40, 32);
      #pragma unroll
      for (int i = 0; i < 5; i++) mbar_init(c.pub + 8 * i, 4);
      #pragma unroll
      for (int i = 5; i < 10; i++) mbar_init(c.xfree + 8 * i, 2);
    }
    asm volatile("fence.mbarrier_init.release.cluster;" ::: "memory");
    if (w0) TL(11);
  }
  __syncwarp();
  asm volatile("barrier.cluster.arrive.relaxed.aligned;" ::: "memory");
  if (c.wg == 2 && c.lane == 0 && !extra) {
    if (w0) {
      #pragma unroll
      for (int kb = 0; kb < DFIRST; kb++) {
        mbar_expect_tx(c.full1 + 8 * kb, 16384);
        tma_load(c.sbase + RING1_OFF + kb * 16384, role < 5 ? &maps.dr : &maps.di, kb * 64, (role < 5 ? role : role - 5) * 128, c.full1 + 8 * kb);
        tma_load(c.sbase + RING1_OFF + kb * 16384 + 8192, role < 5 ? &maps.dr : &maps.di, kb * 64, (role < 5 ? role : role - 5) * 128 + 64, c.full1 + 8 * kb);
      }
      TL(12);
    } else if (w1) {
      #pragma unroll
      for (int i = 0; i < UNI; i++) { mbar_expect_tx(c.xfull + 8 * i, A_CHUNK); tma_load_5d(c.sbase + i * A_CHUNK, &maps.x, i * 64, mb1 * 4, c.xfull + 8 * i); }
      #pragma unroll
      for (int i = UNI; i < 10; i++) mbar_expect_tx(c.xfull + 8 * i, A_CHUNK);
      TL(13);
    }
  }
  __syncwarp();

  if (c.wg == 2) {
    reg_dealloc<40>();
    asm volatile("barrier.cluster.wait.acquire.aligned;" ::: "memory");
    if (w0) {
      if (c.lane == 0) {
        if ((c.sbase & 0x3FFFFu) != 0x400u) asm volatile("trap;");
        int it = extra ? 0 : DFIRST;
        if (DDELAY) __nanosleep(DDELAY);
        prefetch_map(&maps.wg); prefetch_map(&maps.wu); prefetch_map(&maps.di); prefetch_map(&maps.xn);
        #pragma unroll 1
        for (int t = 0; t < nT; t++) {
          const UnitSrc u = unit_src(maps, extra ? 36 : unit_of(role, t));
          #pragma unroll 1
          for (int kb = it - 10 * t; kb < 10; kb++, it++) {
            const int slot = it & 3;
            const uint32_t full = c.full1 + 8 * slot;
            const uint32_t dst = c.sbase + RING1_OFF + slot * 16384;
            mbar_wait(c.empty1 + 8 * slot, ((it >> 2) & 1) ^ 1);
            mbar_expect_tx(full, extra ? 32768 : 16384);
            tma_load(dst, u.m0, u.x0 + kb * u.dx, u.y0 + kb * u.dy, full);
            tma_load(dst + 8192, u.m1, u.x0 + kb * u.dx, u.y1 + kb * u.dy, full);
            if (kb == PFKB && t + 2 < nT && !extra && mb1 < 10) prefetch_unit(maps, unit_of(role, t + 2), mb1);
            if (extra) {
              if (kb == 0) { wait_counter<100>(&p.cnt[(CNT_XN + mb1 + 2 * t) * 32], 8); fence_proxy_async_global(); }
              tma_load(c.sbase + kb * A_CHUNK, &maps.xn, kb * 64, (mb1 + 2 * t) * 128, full);
            }
          }
        }
      }
    } else if (w1) {
      if (c.lane == 0 && !extra) {
        #pragma unroll
        for (int i = UNI / 2; i < 5; i++) {
          if (i >= XAHEAD) mbar_wait(c.xfull + 8 * (2 * (i - XAHEAD) + XW), 0);
          tma_load_5d_mc(c.sbase + (2 * i + rank) * A_CHUNK, &maps.x, (2 * i + rank) * 64, mb1 * 4, c.xfull + 8 * (2 * i + rank));
        }
        #pragma unroll
        for (int i = 0; i < 10; i++) { mbar_wait(c.xfull + 8 * i, 0); mbar_expect_tx(c.xfull + 8 * i, A_CHUNK); }
        TL(14);
        mbar_wait(c.flagb + 32, 0);
        fence_proxy_async_global();
        TL(1);
        #pragma unroll
        for (int i = 0; i < EXP_NRELOAD; i++) {
          mbar_wait(c.xfree + 8 * (2 * i + rank), 0);
          if (i >= XNAHEAD) mbar_wait(c.xfull + 8 * (2 * (i - XNAHEAD) + 1), 1);
          tma_load_mc(c.sbase + (2 * i + rank) * A_CHUNK, &maps.xn, (2 * i + rank) * 64, mb1 * 128, c.xfull + 8 * (2 * i + rank));
        }
        TL(15);
        prefetch_map(&maps.cr); prefetch_map(&maps.ci); prefetch_map(&maps.ab); prefetch_map(&maps.h); prefetch_map(&maps.wd);
        int slot = 0, ph = 0;
        #pragma unroll 1
        for (int i = 0; i < n2; i++) {
          if (PF > 0 && ((i + PF) & 3) == nt && i + PF < nC) { const int kc = c0 + i + PF; tma_prefetch(kc >= 32 ? &maps.ci : &maps.cr, (kc & 31) * 64, mb2 * 128); }
          const uint32_t full = c.full2 + 8 * slot;
          const uint32_t dst = c.sbase + slot * SLOT2;
          mbar_wait(c.empty2 + 8 * slot, ph);
          if (i == 0) { TL(2); mbar_wait(c.flagb, 0); PFENCE; TL(3); }
          if (c0 + i == max(c0, 32)) { mbar_wait(c.flagb + 24, 0); PFENCE; }
          mbar_expect_tx(full, SLOT2);
          if (i < nC) {
            const int kc = c0 + i;
            const int im = kc >= 32;
            const int kk = (kc & 31) * 64;
            tma_load(dst, im ? &maps.ci : &maps.cr, kk, mb2 * 128, full);
            tma_load_mc(dst + 16384 + rank * 10240, &maps.ab, kk, im * 640 + nt * 160 + rank * 80, full);
          } else {
            const int kd = d0 + i - nC;
            tma_load_3d_mc(dst + 16384 + rank * 10240, &maps.wd, kd * 64 + rank * 32, nt * 5, full);
            if (i == nC) { TL(4); mbar_wait(c.flagb + 8, 0); PFENCE; TL(5); }
            if (kd == 26) { mbar_wait(c.flagb + 16, 0); PFENCE; }
            tma_load_3d(dst, &maps.h, kd * 64, mb2 * 2, full);
          }
          if (++slot == R2) { slot = 0; ph ^= 1; }
        }
      }
    } else if (w2) {
      const uint32_t total = D_ * F_ * 2, per = ((total + NUM_CTAS - 1) / NUM_CTAS + 127) & ~127u, beg = blockIdx.x * per;
      if (DPF == 2 && !extra) named_sync(3, 256 + 64);
      if (DPF && c.lane == 0 && !extra && mb1 < 6) prefetch_unit(maps, role, 4 + mb1);
      const uint32_t tag = ld_relaxed(&p.cnt[CNT_EPOCH * 32]) + 1;
      if (!extra) {
        if (PFW >= 0) mbar_wait(c.xfree + 8 * (2 * PFW + rank), 0);
        else __nanosleep(PFNS);
        if (c.lane == 0 && mb1 < 10) prefetch_unit(maps, unit_of(role, 1), mb1);
        __syncwarp();
        {
          const uint4 st = ll_load4(p.ll + mb1 * 128 + 4 * c.lane, tag);
          const uint32_t tb = c.sbase + TAB_OFF + c.lane * 16;
          asm volatile("st.shared.v4.f32 [%0], {%1, %2, %3, %4};" :: "r"(tb), "f"(-bf_lo(st.x)), "f"(-bf_lo(st.y)), "f"(-bf_lo(st.z)), "f"(-bf_lo(st.w)) : "memory");
          asm volatile("st.shared.v4.f32 [%0], {%1, %2, %3, %4};" :: "r"(tb + 512), "f"(rcp_approx(bf_hi(st.x))), "f"(rcp_approx(bf_hi(st.y))),
                       "f"(rcp_approx(bf_hi(st.z))), "f"(rcp_approx(bf_hi(st.w))) : "memory");
          const uint4 ds = ll_load4(p.ll + S_ + role * 128 + 4 * c.lane, tag);
          asm volatile("st.shared.v4.u32 [%0], {%1, %2, %3, %4};" :: "r"(tb + 1024), "r"(ds.x), "r"(ds.y), "r"(ds.z), "r"(ds.w) : "memory");
          mbar_arrive(c.flagb + 40);
          if (c.lane == 0) TL(59);
        }
        mbar_wait(c.flagb + 32, 0);
        if (ZDELAY) __nanosleep(ZDELAY);
        __syncwarp();
        char* zb = reinterpret_cast<char*>(p.out + (size_t)(mb2 * 128 + kh * 64) * D_ + nt * 160);
        char* zf = zb + (c.lane >> 3) * (D_ * 2) + (nt & 1) * 64 + (c.lane & 7) * 16;
        char* zh = zb + (c.lane >> 2) * (D_ * 2) + ((nt & 1) ^ 1) * 256 + (c.lane & 3) * 16;
        #pragma unroll
        for (int j = 0; j < 32; j++) { asm volatile("st.global.v4.u32 [%0], {%1, %1, %1, %1};" :: "l"(zf + (j >> 1) * (4 * D_ * 2) + (j & 1) * 128), "r"(0) : "memory"); pace<PACE_Z>(); }
        #pragma unroll
        for (int j = 0; j < 8; j++) { asm volatile("st.global.v4.u32 [%0], {%1, %1, %1, %1};" :: "l"(zh + j * (8 * D_ * 2)), "r"(0) : "memory"); pace<PACE_Z>(); }
      }
      __syncwarp();
      if (c.lane == 1) {
        __nanosleep(6000);
        if (beg < total) l2_prefetch((const char*)p.wd + beg, min(per, total - beg));
      } else if (c.lane == 0) {
        #pragma unroll 1
        for (int t = 0; t < nT; t++) {
          mbar_wait(c.pub + 8 * t, 0);
          const int unit = unit_of(role, t);
          PUB_RED(&p.cnt[(extra ? CNT_HX + mb1 + 2 * t : unit < 5 ? CNT_A : unit < 10 ? CNT_B : CNT_H + mb1) * 32]);
          TL(35 + t * 4);
        }
      }
    } else {
      if (!extra) {
        named_sync(3, 256 + (DPF == 2 ? 64 : 32));
        if (c.lane == 0) {
          red_release(&p.cnt[(CNT_XN + (blockIdx.x >> 3)) * 32]);
          TL(55);
          wait_counter<50>(&p.cnt[(CNT_XN + mb1) * 32], 8);
          mbar_arrive(c.flagb + 32);
          __nanosleep(2000);
          wait_counter<300>(&p.cnt[CNT_A * 32], 80);           WFENCE; mbar_arrive(c.flagb);
          wait_counter<300>(&p.cnt[CNT_B * 32], 80);           WFENCE; mbar_arrive(c.flagb + 24);
          wait_counter<500>(&p.cnt[(CNT_H + mb2) * 32], 26);   WFENCE; mbar_arrive(c.flagb + 8);
          wait_counter<500>(&p.cnt[(CNT_HX + mb2) * 32], 1);   WFENCE; mbar_arrive(c.flagb + 16);
          if (atomicAdd(&p.cnt[CNT_DONE * 32], 1u) == 127u) {
            for (int i = 0; i < CNT_TOTAL; i++) p.cnt[i * 32] = 0;
            p.cnt[CNT_EPOCH * 32] = ld_relaxed(&p.cnt[CNT_EPOCH * 32]) + 1;
          }
        }
      }
    }
  } else {
    if (!extra) {
      const float sh = bf_lo(x0);
      float s0 = 0.f, s1 = 0.f, q0 = 0.f, q1 = 0.f;
      #pragma unroll
      for (int i = 0; i < 5; i++) {
        const uint32_t w[4] = {v[i].x, v[i].y, v[i].z, v[i].w};
        #pragma unroll
        for (int j = 0; j < 4; j++) { const float a = bf_lo(w[j]) - sh, b = bf_hi(w[j]) - sh; s0 += a; s1 += b; q0 = fmaf(a, a, q0); q1 = fmaf(b, b, q1); }
      }
      float s = s0 + s1, ss = q0 + q1;
      #pragma unroll
      for (int o = 1; o < 16; o <<= 1) { s += __shfl_xor_sync(0xffffffffu, s, o); ss += __shfl_xor_sync(0xffffffffu, ss, o); }
      const float dm = s * (1.0f / D_);
      const float var = fmaxf(fmaf(-dm, dm, ss * (1.0f / D_)), 0.f);
      float sd, inv;
      asm("sqrt.approx.f32 %0, %1;" : "=f"(sd) : "f"(round_bf(round_bf(var) + 1e-5f)));
      sd = round_bf(sd);
      inv = rcp_approx(sd);
      const float ih = round_bf(inv);
      const uint32_t m2 = pack_bf16(sh + dm, sh + dm), ih2 = pack_bf16(ih, ih), il2 = pack_bf16(inv - ih, inv - ih);
      uint4* dst = reinterpret_cast<uint4*>(p.xn + (size_t)xn_row(tok) * D_);
      #pragma unroll
      for (int i = 0; i < 5; i++)
        dst[l16 + 16 * i] = make_uint4(norm2(v[i].x, m2, ih2, il2), norm2(v[i].y, m2, ih2, il2), norm2(v[i].z, m2, ih2, il2), norm2(v[i].w, m2, ih2, il2));
      if (l16 == 0) ll_store(p.ll + tok, (m2 & 0xffffu) | __float_as_uint(sd), epoch);
      named_arrive(3, 256 + (DPF == 2 ? 64 : 32));
      if (c.elect) TL(52 + c.wg);
      if (c.wg == 1) {
        const int drow = blockIdx.x * 8 + ((threadIdx.x >> 4) & 7);
        const uint4* ds = reinterpret_cast<const uint4*>(drow < D_ ? p.dr + drow * D_ : p.di + (drow - D_) * D_) + l16;
        uint4 dv[5];
        #pragma unroll
        for (int i = 0; i < 5; i++) dv[i] = __ldg(ds + 16 * i);
        float sa = ((sum8(dv[0]) + sum8(dv[1])) + (sum8(dv[2]) + sum8(dv[3]))) + sum8(dv[4]);
        #pragma unroll
        for (int o = 1; o < 16; o <<= 1) sa += __shfl_xor_sync(0xffffffffu, sa, o);
        if (l16 == 0) ll_store(p.ll + S_ + drow, __float_as_uint(sa), epoch);
      }
    }
    reg_alloc<232>();
    asm volatile("barrier.cluster.wait.acquire.aligned;" ::: "memory");
    if (threadIdx.x == 0) TL(54);

    const int rl = c.warp * 16 + (c.lane >> 2);
    const int nT1 = extra ? nT : nT - 1;
    if (c.wg == 0 && !extra) {
      float acc[2][64];
      if (role < 5) stage1_mma<0, false, true>(c, acc, 0, false, true, false);
      else          stage1_mma<1, false, true>(c, acc, 0, false, true, false);
      mbar_wait(c.flagb + 40, 0);
      store_ab_raw(c, acc, reinterpret_cast<uint4*>(p.abT + (size_t)(role * 128 + rl) * S_ + mb1 * 128 + (c.lane & 3) * 8), rl, role < 5 ? 1.0f : -1.0f);
      publish(c, 0);
    }
    #pragma unroll 1
    for (int t = (c.wg == 0 && !extra) ? 2 : c.wg; t < nT1; t += 2) {
      const int unit = extra ? 36 : unit_of(role, t);
      const int col = (extra ? mb1 + 2 * t : mb1) * 128 + (c.lane & 3) * 8;
      if (t > 0) named_sync(1 + c.wg, 256);
      const bool free_all = !extra && t == nT - 2;
      const bool has_next = t < nT - 1;
      float acc[2][64];
      if (unit < 10) {
        stage1_mma<1, false, false>(c, acc, t * 10, true, has_next, free_all);
        store_ab(acc, reinterpret_cast<uint4*>(p.abT + ROWOFF(unit * 128, rl, col)));
      } else {
        stage1_mma<2, false, false>(c, acc, t * 10, t == 1 && !extra, has_next, free_all);
        uint4* dst = reinterpret_cast<uint4*>(p.hT + ROWOFF((unit - 10) * 64, rl, col));
        #pragma unroll
        for (int sl = 0; sl < 8; sl++) {
          #pragma unroll 1
          for (int z = c.zero; z < 1; z++) store_h_slice(acc, dst, sl, __int_as_float(0xbfb8aa3b + z));
          if (sl < 7) pace<PACE_H>();
        }
      }
      publish(c, t);
    }

    if (!extra) {
      OutAddr o;
      uint4 xr[10];
      {
        const uint32_t stg = c.sbase + c.warp * SLOT2 + c.wg * 8192;
        const int rf = c.lane >> 3, cf = (nt & 1) * 64 + (c.lane & 7) * 16;
        const int rh = (c.lane >> 3) + (c.lane & 4), ch = ((nt & 1) ^ 1) * 256 + (c.lane & 3) * 16;
        const size_t ob = ((size_t)(mb2 * 128 + c.wg * 64 + c.warp * 16) * D_ + nt * 160) * 2;
        o.sw = stg + (c.lane & 15) * 336 + (c.lane >> 4) * 16;
        o.lf = stg + rf * 336 + cf; o.lh = stg + rh * 336 + ch;
        o.gf = reinterpret_cast<char*>(p.out) + ob + rf * (D_ * 2) + cf; o.gh = reinterpret_cast<char*>(p.out) + ob + rh * (D_ * 2) + ch;
        asm volatile("" : "+r"(o.sw), "+r"(o.lf), "+r"(o.lh), "+l"(o.gf), "+l"(o.gh));
        const char* xf = reinterpret_cast<const char*>(p.x) + ob + rf * (D_ * 2) + cf;
        const char* xh = reinterpret_cast<const char*>(p.x) + ob + rh * (D_ * 2) + ch;
        #pragma unroll
        for (int i = 0; i < 10; i++) xr[i] = make_uint4(0u, 0u, 0u, 0u);
        if (c.wg == EARLYWG) {
          #pragma unroll
          for (int i = 0; i < 10; i++) xr[i] = __ldg(reinterpret_cast<const uint4*>(i < 8 ? xf + (i >> 1) * (4 * D_ * 2) + (i & 1) * 128 : xh + (i - 8) * (8 * D_ * 2)));
        }
      }
      float acc[80];
      int i0 = 0;
      if (((nT - 1) & 1) == c.wg) {
        const int t = nT - 1;
        named_sync(1 + c.wg, 256);
        uint32_t gu[2][32];
        {
          float acc1[2][64];
          stage1_mma<2, true, false>(c, acc1, t * 10, false, true, false);
          #pragma unroll
          for (int r = 0; r < 32; r++) { gu[0][r] = pack_bf16(acc1[0][2 * r], acc1[0][2 * r + 1]); gu[1][r] = pack_bf16(acc1[1][2 * r], acc1[1][2 * r + 1]); }
        }
        #pragma unroll
        for (int r = 0; r < 80; r++) acc[r] = 0.f;
        uint4* dst = reinterpret_cast<uint4*>(p.hT + ROWOFF((unit_of(role, t) - 10) * 64, rl, mb1 * 128 + (c.lane & 3) * 8));
        if (c.elect) TL(20 + c.wg);
        #pragma unroll
        for (int i = 0; i < 8; i++) {
          stage2_kb<false>(c, acc, i % R2, i / R2, (i + R2 - 1) % R2, i > 0, i);
          uint32_t w[4];
          #pragma unroll
          for (int b = 0; b < 4; b++) {
            const int r = 8 * (i & 3) + 2 * b + (i >> 2);
            w[b] = pack_bf16(silu_mul(bf_lo(gu[0][r]), bf_lo(gu[1][r])), silu_mul(bf_hi(gu[0][r]), bf_hi(gu[1][r])));
          }
          ST_H(dst, (i >> 2), (i & 3)) make_uint4(w[0], w[1], w[2], w[3]);
        }
        publish(c, t);
        wgmma_wait<0>();
        fence_acc(acc);
        i0 = 8;
      }
      if (i0 == 0) {
        #pragma unroll
        for (int r = 0; r < 80; r++) acc[r] = 0.f;
        named_sync(1 + c.wg, 256);
        if (c.elect) TL(20 + c.wg);
      }
      int slot = i0 % R2, ph = i0 / R2, prev = (i0 + R2 - 1) % R2;
      #pragma unroll 1
      for (int i = i0; i < nC; i++) {
        stage2_kb<false>(c, acc, slot, ph, prev, i > 0, i);
        prev = slot;
        if (++slot == R2) { slot = 0; ph ^= 1; }
      }
      if (c.elect) TL(22 + c.wg);
      #pragma unroll 1
      for (int i = nC; i < n2; i++) {
        if (STAG > 0 && i == n2 - STAG && c.wg != EARLYWG) {
          wgmma_wait<0>();
          if (STAG == R2) release2(c, prev);
          named_sync(4, 256);
        }
        if (EARLY_ARV && i == n2 - 1 && c.wg == EARLYWG) named_arrive(4, 256);
        stage2_kb<true>(c, acc, slot, ph, prev, i - 1 < n2 - R2 && !(STAG == R2 && c.wg != EARLYWG && i == n2 - STAG), i);
        prev = slot;
        if (++slot == R2) { slot = 0; ph ^= 1; }
      }
      if (!EARLY_ARV && STAG > 0 && c.wg == EARLYWG) named_arrive(4, 256);
      wgmma_wait<0>();
      fence_acc(acc);
      if (c.elect) { TL(24 + c.wg); T2(64 + c.wg * 64 + n2); }
      stage2_finish(acc, o, xr, c.wg == EARLYWG);

      if (c.elect) { TL(28 + c.wg); T2(64 + c.wg * 64 + n2 + 1); }
    }
  }
}

typedef CUresult (*PFN_encodeTiled)(CUtensorMap*, CUtensorMapDataType, cuuint32_t, void*, const cuuint64_t*, const cuuint64_t*,
                                    const cuuint32_t*, const cuuint32_t*, CUtensorMapInterleave, CUtensorMapSwizzle,
                                    CUtensorMapL2promotion, CUtensorMapFloatOOBfill);

void make_map(PFN_encodeTiled enc, CUtensorMap* m, const void* ptr, uint64_t rows, uint64_t cols, uint32_t box_rows, uint32_t box_cols, CUtensorMapSwizzle sw) {
  cuuint64_t dims[2] = {cols, rows};
  cuuint64_t strides[1] = {cols * 2};
  cuuint32_t box[2] = {box_cols, box_rows};
  cuuint32_t es[2] = {1, 1};
  enc(m, CU_TENSOR_MAP_DATA_TYPE_BFLOAT16, 2, const_cast<void*>(ptr), dims, strides, box, es, CU_TENSOR_MAP_INTERLEAVE_NONE, sw,
      CU_TENSOR_MAP_L2_PROMOTION_L2_256B, CU_TENSOR_MAP_FLOAT_OOB_FILL_NONE);
}
void make_map3(PFN_encodeTiled enc, CUtensorMap* m, const void* ptr, uint64_t rows, uint64_t cols, uint32_t box_rows, uint32_t box_cols, uint32_t nblk, CUtensorMapSwizzle sw) {
  cuuint64_t dims[3] = {box_cols, rows, cols / box_cols};
  cuuint64_t strides[2] = {cols * 2, (cuuint64_t)box_cols * 2};
  cuuint32_t box[3] = {box_cols, box_rows, nblk};
  cuuint32_t es[3] = {1, 1, 1};
  enc(m, CU_TENSOR_MAP_DATA_TYPE_BFLOAT16, 3, const_cast<void*>(ptr), dims, strides, box, es, CU_TENSOR_MAP_INTERLEAVE_NONE, sw,
      CU_TENSOR_MAP_L2_PROMOTION_L2_256B, CU_TENSOR_MAP_FLOAT_OOB_FILL_NONE);
}

}

extern "C" void kernel_launch(void* const* d_in, const int* in_sizes, int n_in, void* d_out, int out_size) {
  (void)in_sizes; (void)n_in; (void)out_size;
  PFN_encodeTiled enc = nullptr;
  cudaDriverEntryPointQueryResult qres;
  cudaGetDriverEntryPoint("cuTensorMapEncodeTiled", (void**)&enc, cudaEnableDefault, &qres);
  Params p;
  p.x = (const __nv_bfloat16*)d_in[0]; p.out = (__nv_bfloat16*)d_out;
  cudaGetSymbolAddress((void**)&p.xn, g_xn); cudaGetSymbolAddress((void**)&p.ll, g_ll); cudaGetSymbolAddress((void**)&p.cnt, g_cnt);
  cudaGetSymbolAddress((void**)&p.abT, g_abT); cudaGetSymbolAddress((void**)&p.hT, g_hT);
  p.cr = (const __nv_bfloat16*)d_in[1]; p.ci = (const __nv_bfloat16*)d_in[2];
  p.dr = (const __nv_bfloat16*)d_in[3]; p.di = (const __nv_bfloat16*)d_in[4];
  p.wg = (const __nv_bfloat16*)d_in[6]; p.wu = (const __nv_bfloat16*)d_in[7]; p.wd = (const __nv_bfloat16*)d_in[8];
  Maps maps;
  {
    cuuint64_t dims[5] = {(cuuint64_t)D_, 2, 4, 4, (cuuint64_t)(S_ / 32)};
    cuuint64_t strides[4] = {(cuuint64_t)D_ * 2, (cuuint64_t)D_ * 2 * 8, (cuuint64_t)D_ * 2 * 2, (cuuint64_t)D_ * 2 * 32};
    cuuint32_t box[5] = {64, 2, 4, 4, 4};
    cuuint32_t es[5] = {1, 1, 1, 1, 1};
    enc(&maps.x, CU_TENSOR_MAP_DATA_TYPE_BFLOAT16, 5, d_in[0], dims, strides, box, es, CU_TENSOR_MAP_INTERLEAVE_NONE,
        CU_TENSOR_MAP_SWIZZLE_128B, CU_TENSOR_MAP_L2_PROMOTION_L2_256B, CU_TENSOR_MAP_FLOAT_OOB_FILL_NONE);
  }
  make_map(enc, &maps.xn, p.xn, S_, D_, 128, 64, CU_TENSOR_MAP_SWIZZLE_128B);
  make_map(enc, &maps.dr, d_in[3], D_, D_, 64, 64, CU_TENSOR_MAP_SWIZZLE_128B);
  make_map(enc, &maps.di, d_in[4], D_, D_, 64, 64, CU_TENSOR_MAP_SWIZZLE_128B);
  make_map(enc, &maps.wg, d_in[6], D_, F_, 64, 64, CU_TENSOR_MAP_SWIZZLE_128B);
  make_map(enc, &maps.wu, d_in[7], D_, F_, 64, 64, CU_TENSOR_MAP_SWIZZLE_128B);
  make_map(enc, &maps.cr, d_in[1], S_, S_, 128, 64, CU_TENSOR_MAP_SWIZZLE_128B);
  make_map(enc, &maps.ci, d_in[2], S_, S_, 128, 64, CU_TENSOR_MAP_SWIZZLE_128B);
  make_map3(enc, &maps.h, p.hT, F_, S_, 64, 64, 2, CU_TENSOR_MAP_SWIZZLE_128B);
  make_map(enc, &maps.ab, p.abT, 2 * D_, S_, 80, 64, CU_TENSOR_MAP_SWIZZLE_128B);
  make_map3(enc, &maps.wd, d_in[8], F_, D_, 32, 32, 5, CU_TENSOR_MAP_SWIZZLE_64B);
  cudaFuncSetAttribute(fused_kernel, cudaFuncAttributeMaxDynamicSharedMemorySize, SMEM_BYTES);
  cudaLaunchConfig_t cfg = {};
  cfg.gridDim = dim3(NUM_CTAS); cfg.blockDim = dim3(384); cfg.dynamicSmemBytes = SMEM_BYTES; cfg.stream = cudaStreamPerThread;
  cudaLaunchAttribute at[1];
  at[0].id = cudaLaunchAttributeClusterDimension; at[0].val.clusterDim.x = 2; at[0].val.clusterDim.y = 1; at[0].val.clusterDim.z = 1;
  cfg.attrs = at; cfg.numAttrs = 1;
  cudaLaunchKernelEx(&cfg, fused_kernel, p, maps);
}
```

```cpp
#include <cuda_runtime.h>
#include <cuda_bf16.h>
#include <cuda.h>
#include <stdint.h>

template<int TA, int TB, int SA> __device__ __forceinline__ void wgmma_ss_n128(float (&d)[64], uint64_t da, uint64_t db, int sd) {
  asm volatile("{\n.reg .pred p;\nsetp.ne.b32 p, %66, 0;\n"
    "wgmma.mma_async.sync.aligned.m64n128k16.f32.bf16.bf16 {%0, %1, %2, %3, %4, %5, %6, %7, %8, %9, %10, %11, %12, %13, %14, %15, %16, %17, %18, %19, %20, %21, %22, %23, %24, %25, %26, %27, %28, %29, %30, %31, %32, %33, %34, %35, %36, %37, %38, %39, %40, %41, %42, %43, %44, %45, %46, %47, %48, %49, %50, %51, %52, %53, %54, %55, %56, %57, %58, %59, %60, %61, %62, %63}, %64, %65, p, %69, 1, %67, %68;\n}\n"
    : "+f"(d[0]), "+f"(d[1]), "+f"(d[2]), "+f"(d[3]), "+f"(d[4]), "+f"(d[5]), "+f"(d[6]), "+f"(d[7]), "+f"(d[8]), "+f"(d[9]), "+f"(d[10]), "+f"(d[11]), "+f"(d[12]), "+f"(d[13]), "+f"(d[14]), "+f"(d[15]), "+f"(d[16]), "+f"(d[17]), "+f"(d[18]), "+f"(d[19]), "+f"(d[20]), "+f"(d[21]), "+f"(d[22]), "+f"(d[23]), "+f"(d[24]), "+f"(d[25]), "+f"(d[26]), "+f"(d[27]), "+f"(d[28]), "+f"(d[29]), "+f"(d[30]), "+f"(d[31]), "+f"(d[32]), "+f"(d[33]), "+f"(d[34]), "+f"(d[35]), "+f"(d[36]), "+f"(d[37]), "+f"(d[38]), "+f"(d[39]), "+f"(d[40]), "+f"(d[41]), "+f"(d[42]), "+f"(d[43]), "+f"(d[44]), "+f"(d[45]), "+f"(d[46]), "+f"(d[47]), "+f"(d[48]), "+f"(d[49]), "+f"(d[50]), "+f"(d[51]), "+f"(d[52]), "+f"(d[53]), "+f"(d[54]), "+f"(d[55]), "+f"(d[56]), "+f"(d[57]), "+f"(d[58]), "+f"(d[59]), "+f"(d[60]), "+f"(d[61]), "+f"(d[62]), "+f"(d[63])
    : "l"(da), "l"(db), "r"(sd), "n"(TA), "n"(TB), "n"(SA));
}
template<int TA, int TB, int SA> __device__ __forceinline__ void wgmma_ss_n160(float (&d)[80], uint64_t da, uint64_t db, int sd) {
  asm volatile("{\n.reg .pred p;\nsetp.ne.b32 p, %82, 0;\n"
    "wgmma.mma_async.sync.aligned.m64n160k16.f32.bf16.bf16 {%0, %1, %2, %3, %4, %5, %6, %7, %8, %9, %10, %11, %12, %13, %14, %15, %16, %17, %18, %19, %20, %21, %22, %23, %24, %25, %26, %27, %28, %29, %30, %31, %32, %33, %34, %35, %36, %37, %38, %39, %40, %41, %42, %43, %44, %45, %46, %47, %48, %49, %50, %51, %52, %53, %54, %55, %56, %57, %58, %59, %60, %61, %62, %63, %64, %65, %66, %67, %68, %69, %70, %71, %72, %73, %74, %75, %76, %77, %78, %79}, %80, %81, p, %85, 1, %83, %84;\n}\n"
    : "+f"(d[0]), "+f"(d[1]), "+f"(d[2]), "+f"(d[3]), "+f"(d[4]), "+f"(d[5]), "+f"(d[6]), "+f"(d[7]), "+f"(d[8]), "+f"(d[9]), "+f"(d[10]), "+f"(d[11]), "+f"(d[12]), "+f"(d[13]), "+f"(d[14]), "+f"(d[15]), "+f"(d[16]), "+f"(d[17]), "+f"(d[18]), "+f"(d[19]), "+f"(d[20]), "+f"(d[21]), "+f"(d[22]), "+f"(d[23]), "+f"(d[24]), "+f"(d[25]), "+f"(d[26]), "+f"(d[27]), "+f"(d[28]), "+f"(d[29]), "+f"(d[30]), "+f"(d[31]), "+f"(d[32]), "+f"(d[33]), "+f"(d[34]), "+f"(d[35]), "+f"(d[36]), "+f"(d[37]), "+f"(d[38]), "+f"(d[39]), "+f"(d[40]), "+f"(d[41]), "+f"(d[42]), "+f"(d[43]), "+f"(d[44]), "+f"(d[45]), "+f"(d[46]), "+f"(d[47]), "+f"(d[48]), "+f"(d[49]), "+f"(d[50]), "+f"(d[51]), "+f"(d[52]), "+f"(d[53]), "+f"(d[54]), "+f"(d[55]), "+f"(d[56]), "+f"(d[57]), "+f"(d[58]), "+f"(d[59]), "+f"(d[60]), "+f"(d[61]), "+f"(d[62]), "+f"(d[63]), "+f"(d[64]), "+f"(d[65]), "+f"(d[66]), "+f"(d[67]), "+f"(d[68]), "+f"(d[69]), "+f"(d[70]), "+f"(d[71]), "+f"(d[72]), "+f"(d[73]), "+f"(d[74]), "+f"(d[75]), "+f"(d[76]), "+f"(d[77]), "+f"(d[78]), "+f"(d[79])
    : "l"(da), "l"(db), "r"(sd), "n"(TA), "n"(TB), "n"(SA));
}
template<int TB> __device__ __forceinline__ void wgmma_rs_n128(float (&d)[64], uint32_t a0, uint32_t a1, uint32_t a2, uint32_t a3, uint64_t db, int sd) {
  asm volatile("{\n.reg .pred p;\nsetp.ne.b32 p, %69, 0;\n"
    "wgmma.mma_async.sync.aligned.m64n128k16.f32.bf16.bf16 {%0, %1, %2, %3, %4, %5, %6, %7, %8, %9, %10, %11, %12, %13, %14, %15, %16, %17, %18, %19, %20, %21, %22, %23, %24, %25, %26, %27, %28, %29, %30, %31, %32, %33, %34, %35, %36, %37, %38, %39, %40, %41, %42, %43, %44, %45, %46, %47, %48, %49, %50, %51, %52, %53, %54, %55, %56, %57, %58, %59, %60, %61, %62, %63}, {%64, %65, %66, %67}, %68, p, 1, 1, %70;\n}\n"
    : "+f"(d[0]), "+f"(d[1]), "+f"(d[2]), "+f"(d[3]), "+f"(d[4]), "+f"(d[5]), "+f"(d[6]), "+f"(d[7]), "+f"(d[8]), "+f"(d[9]), "+f"(d[10]), "+f"(d[11]), "+f"(d[12]), "+f"(d[13]), "+f"(d[14]), "+f"(d[15]), "+f"(d[16]), "+f"(d[17]), "+f"(d[18]), "+f"(d[19]), "+f"(d[20]), "+f"(d[21]), "+f"(d[22]), "+f"(d[23]), "+f"(d[24]), "+f"(d[25]), "+f"(d[26]), "+f"(d[27]), "+f"(d[28]), "+f"(d[29]), "+f"(d[30]), "+f"(d[31]), "+f"(d[32]), "+f"(d[33]), "+f"(d[34]), "+f"(d[35]), "+f"(d[36]), "+f"(d[37]), "+f"(d[38]), "+f"(d[39]), "+f"(d[40]), "+f"(d[41]), "+f"(d[42]), "+f"(d[43]), "+f"(d[44]), "+f"(d[45]), "+f"(d[46]), "+f"(d[47]), "+f"(d[48]), "+f"(d[49]), "+f"(d[50]), "+f"(d[51]), "+f"(d[52]), "+f"(d[53]), "+f"(d[54]), "+f"(d[55]), "+f"(d[56]), "+f"(d[57]), "+f"(d[58]), "+f"(d[59]), "+f"(d[60]), "+f"(d[61]), "+f"(d[62]), "+f"(d[63])
    : "r"(a0), "r"(a1), "r"(a2), "r"(a3), "l"(db), "r"(sd), "n"(TB));
}

namespace {

constexpr int S_ = 2048, D_ = 640, F_ = 1728;
constexpr int A_CHUNK   = 16384;
constexpr int RING1_OFF = 10 * A_CHUNK;
constexpr int R1        = 4;
constexpr int SLOT2     = 36864;
constexpr int R2        = 6;
constexpr int BAR_OFF   = RING1_OFF + R1 * 16384;
constexpr int TAB_OFF   = BAR_OFF + 384;
constexpr int SUM_OFF   = TAB_OFF + 2048;
constexpr int SMEM_BYTES = SUM_OFF + 640;
constexpr int NUM_CTAS  = 132;
#define NC1 37
#define ND1 13

constexpr int XE = 3;

__device__ __align__(16) unsigned long long g_ll[S_ + 37 * 128];
__device__ __align__(1024) __nv_bfloat16 g_abT[2 * D_ * S_];
__device__ __align__(1024) __nv_bfloat16 g_hT[F_ * S_];
constexpr int CNT_H = 0, CNT_HX = 16, CNT_A = 32, CNT_B = 33, CNT_DONE = 34, CNT_TOTAL = 35, CNT_EPOCH = 35;
__device__ unsigned g_cnt[(CNT_TOTAL + 1) * 32];

struct Params {
  __nv_bfloat16* out;
  unsigned long long* ll; unsigned* cnt; __nv_bfloat16* abT; __nv_bfloat16* hT;
  const __nv_bfloat16* wd;
  const char* pf[5];
};
struct Maps {
  CUtensorMap x, o, dr, di, wg, wu, cr, ci, h, ab, wd;
};

__device__ __forceinline__ uint32_t smem_u32(const void* p) { return (uint32_t)__cvta_generic_to_shared(p); }
__device__ __forceinline__ void mbar_init(uint32_t bar, uint32_t count) { asm volatile("mbarrier.init.shared::cta.b64 [%0], %1;" :: "r"(bar), "r"(count)); }
__device__ __forceinline__ void mbar_expect_tx(uint32_t bar, uint32_t bytes) { asm volatile("mbarrier.arrive.expect_tx.shared::cta.b64 _, [%0], %1;" :: "r"(bar), "r"(bytes) : "memory"); }
__device__ __forceinline__ void mbar_arrive(uint32_t bar) { asm volatile("mbarrier.arrive.shared::cta.b64 _, [%0];" :: "r"(bar) : "memory"); }
__device__ __forceinline__ void mbar_arrive_cta(uint32_t bar, uint32_t cta) {
  asm volatile("{\n.reg .b32 ra;\nmapa.shared::cluster.u32 ra, %0, %1;\nmbarrier.arrive.shared::cluster.b64 _, [ra];\n}\n" :: "r"(bar), "r"(cta) : "memory");
}
__device__ __forceinline__ void mbar_arrive_if(uint32_t bar, uint32_t pred) {
  asm volatile("{\n.reg .pred p;\nsetp.ne.u32 p, %1, 0;\n@p mbarrier.arrive.shared::cta.b64 _, [%0];\n}\n" :: "r"(bar), "r"(pred) : "memory");
}
__device__ __forceinline__ void mbar_arrive_cta_if(uint32_t bar, uint32_t cta, uint32_t pred) {
  asm volatile("{\n.reg .pred p;\n.reg .b32 ra;\nsetp.ne.u32 p, %2, 0;\nmapa.shared::cluster.u32 ra, %0, %1;\n@p mbarrier.arrive.shared::cluster.b64 _, [ra];\n}\n" :: "r"(bar), "r"(cta), "r"(pred) : "memory");
}
__device__ __forceinline__ void mbar_wait(uint32_t bar, uint32_t parity) {
  asm volatile("{\n.reg .pred p;\n.reg .u32 n;\nmov.u32 n, 0;\n"
    "LAB_WAIT:\n"
    "mbarrier.try_wait.parity.shared::cta.b64 p, [%0], %1;\n"
    "@p bra LAB_DONE;\n"
    "add.u32 n, n, 1;\n"
    "setp.lt.u32 p, n, 4000000;\n"
    "@p bra LAB_WAIT;\n"
    "trap;\n"
    "LAB_DONE:\n}\n" :: "r"(bar), "r"(parity) : "memory");
}
__device__ __forceinline__ void tma_load(uint32_t dst, const CUtensorMap* map, int c0, int c1, uint32_t bar) {
  asm volatile("cp.async.bulk.tensor.2d.shared::cluster.global.mbarrier::complete_tx::bytes [%0], [%1, {%3, %4}], [%2];"
    :: "r"(dst), "l"(map), "r"(bar), "r"(c0), "r"(c1) : "memory");
}
__device__ __forceinline__ void tma_load_stream(uint32_t dst, const CUtensorMap* map, int c0, int c1, uint32_t bar, uint64_t pol) {
  asm volatile("cp.async.bulk.tensor.2d.shared::cluster.global.mbarrier::complete_tx::bytes.L2::cache_hint [%0], [%1, {%3, %4}], [%2], %5;"
    :: "r"(dst), "l"(map), "r"(bar), "r"(c0), "r"(c1), "l"(pol) : "memory");
}
__device__ __forceinline__ void tma_load_mc(uint32_t dst, const CUtensorMap* map, int c0, int c1, uint32_t bar) {
  asm volatile("cp.async.bulk.tensor.2d.shared::cluster.global.mbarrier::complete_tx::bytes.multicast::cluster [%0], [%1, {%3, %4}], [%2], %5;"
    :: "r"(dst), "l"(map), "r"(bar), "r"(c0), "r"(c1), "h"((uint16_t)3) : "memory");
}
__device__ __forceinline__ void tma_load_3d(uint32_t dst, const CUtensorMap* map, int c1, int c2, uint32_t bar) {
  asm volatile("cp.async.bulk.tensor.3d.shared::cluster.global.mbarrier::complete_tx::bytes [%0], [%1, {%5, %3, %4}], [%2];"
    :: "r"(dst), "l"(map), "r"(bar), "r"(c1), "r"(c2), "r"(0) : "memory");
}
__device__ __forceinline__ void tma_load_3d_mc(uint32_t dst, const CUtensorMap* map, int c1, int c2, uint32_t bar) {
  asm volatile("cp.async.bulk.tensor.3d.shared::cluster.global.mbarrier::complete_tx::bytes.multicast::cluster [%0], [%1, {%5, %3, %4}], [%2], %6;"
    :: "r"(dst), "l"(map), "r"(bar), "r"(c1), "r"(c2), "r"(0), "h"((uint16_t)3) : "memory");
}
__device__ __forceinline__ void tma_load_5d(uint32_t dst, const CUtensorMap* map, int c0, int c4, uint32_t bar) {
  asm volatile("cp.async.bulk.tensor.5d.shared::cluster.global.mbarrier::complete_tx::bytes [%0], [%1, {%3, %5, %5, %5, %4}], [%2];"
    :: "r"(dst), "l"(map), "r"(bar), "r"(c0), "r"(c4), "r"(0) : "memory");
}
__device__ __forceinline__ void prefetch_map(const CUtensorMap* map) { asm volatile("prefetch.tensormap [%0];" :: "l"(map) : "memory"); }
__device__ __forceinline__ bool elect_one() {
  uint32_t p;
  asm volatile("{\n.reg .pred p;\nelect.sync _|p, 0xffffffff;\nselp.u32 %0, 1, 0, p;\n}\n" : "=r"(p));
  return p != 0;
}
__device__ __forceinline__ void wgmma_fence() { asm volatile("wgmma.fence.sync.aligned;" ::: "memory"); }
__device__ __forceinline__ void wgmma_commit() { asm volatile("wgmma.commit_group.sync.aligned;" ::: "memory"); }
template<int N> __device__ __forceinline__ void wgmma_wait() { asm volatile("wgmma.wait_group.sync.aligned %0;" :: "n"(N) : "memory"); }
template<int N> __device__ __forceinline__ void fence_acc(float (&d)[N]) {
  #pragma unroll
  for (int i = 0; i < N; i++) asm volatile("" : "+f"(d[i]) :: "memory");
}
__device__ __forceinline__ void named_sync(int id, int n) { asm volatile("bar.sync %0, %1;" :: "r"(id), "r"(n) : "memory"); }
__device__ __forceinline__ void named_arrive(int id, int n) { asm volatile("bar.arrive %0, %1;" :: "r"(id), "r"(n) : "memory"); }
template<int R> __device__ __forceinline__ void reg_alloc() { asm volatile("setmaxnreg.inc.sync.aligned.u32 %0;" :: "n"(R)); }
template<int R> __device__ __forceinline__ void reg_dealloc() { asm volatile("setmaxnreg.dec.sync.aligned.u32 %0;" :: "n"(R)); }
__device__ __forceinline__ void fence_proxy_async_global() { asm volatile("fence.proxy.async.global;" ::: "memory"); }
template<int NS> __device__ __forceinline__ void pace() { asm volatile("nanosleep.u32 %0;" :: "n"(NS) : "memory"); }
__device__ __forceinline__ void red_release(unsigned* p) { asm volatile("red.release.gpu.global.add.u32 [%0], 1;" :: "l"(p) : "memory"); }
__device__ __forceinline__ unsigned ld_relaxed(const unsigned* p) { unsigned v; asm volatile("ld.relaxed.gpu.global.u32 %0, [%1];" : "=r"(v) : "l"(p) : "memory"); return v; }
__device__ __forceinline__ void ll_store(unsigned long long* p, uint32_t v, uint32_t epoch) {
  asm volatile("{\n.reg .b64 w;\n.reg .u32 t;\nadd.u32 t, %2, 1;\nmov.b64 w, {%1, t};\nst.relaxed.gpu.global.b64 [%0], w;\n}\n" :: "l"(p), "r"(v), "r"(epoch) : "memory");
}
__device__ __forceinline__ uint4 ll_load4(const unsigned long long* p, uint32_t tag) {
  uint4 v;
  asm volatile("{\n.reg .pred p;\n.reg .u32 n, t0, t1, t2, t3;\n.reg .b64 w0, w1, w2, w3;\nmov.u32 n, 0;\n"
    "LAB_WAIT:\n"
    "ld.relaxed.gpu.global.b64 w0, [%4];\nld.relaxed.gpu.global.b64 w1, [%4 + 256];\n"
    "ld.relaxed.gpu.global.b64 w2, [%4 + 512];\nld.relaxed.gpu.global.b64 w3, [%4 + 768];\n"
    "mov.b64 {%0, t0}, w0;\nmov.b64 {%1, t1}, w1;\nmov.b64 {%2, t2}, w2;\nmov.b64 {%3, t3}, w3;\n"
    "xor.b32 t0, t0, %5;\nxor.b32 t1, t1, %5;\nxor.b32 t2, t2, %5;\nxor.b32 t3, t3, %5;\n"
    "or.b32 t0, t0, t1;\nor.b32 t2, t2, t3;\nor.b32 t0, t0, t2;\n"
    "setp.eq.u32 p, t0, 0;\n"
    "vote.sync.all.pred p, p, 0xffffffff;\n"
    "@p bra.uni LAB_DONE;\n"
    "nanosleep.u32 100;\n"
    "add.u32 n, n, 1;\n"
    "setp.lt.u32 p, n, 2000000;\n"
    "@p bra.uni LAB_WAIT;\n"
    "trap;\n"
    "LAB_DONE:\n}\n" : "=&r"(v.x), "=&r"(v.y), "=&r"(v.z), "=&r"(v.w) : "l"(p), "r"(tag) : "memory");
  return v;
}
template<int TA> __device__ __forceinline__ void wgmma_ss_n8(float (&d)[4], uint64_t da, uint64_t db, int sd) {
  asm volatile("{\n.reg .pred p;\nsetp.ne.b32 p, %6, 0;\n"
    "wgmma.mma_async.sync.aligned.m64n8k16.f32.bf16.bf16 {%0, %1, %2, %3}, %4, %5, p, 1, 1, %7, 0;\n}\n"
    : "+f"(d[0]), "+f"(d[1]), "+f"(d[2]), "+f"(d[3]) : "l"(da), "l"(db), "r"(sd), "n"(TA));
}
template<int SLEEP_NS>
__device__ __forceinline__ void wait_counter(const unsigned* p, unsigned target) {
  asm volatile("{\n.reg .pred p;\n.reg .u32 n, v;\nmov.u32 n, 0;\n"
    "LAB_WAIT:\n"
    "ld.acquire.gpu.global.u32 v, [%0];\n"
    "setp.ge.u32 p, v, %1;\n"
    "@p bra LAB_DONE;\n"
    "nanosleep.u32 %2;\n"
    "add.u32 n, n, 1;\n"
    "setp.lt.u32 p, n, 2000000;\n"
    "@p bra LAB_WAIT;\n"
    "trap;\n"
    "LAB_DONE:\n}\n" :: "l"(p), "r"(target), "n"(SLEEP_NS) : "memory");
}
constexpr uint32_t HI_SW128 = (1024 >> 4) | (1u << 30);
constexpr uint32_t HI_SW64  = (512 >> 4) | (2u << 30);
constexpr uint32_t HI_SW64K = (1024 >> 4) | (2u << 30);
constexpr uint32_t DBASE    = 0x400 >> 4;
constexpr uint32_t LBO_NONE = 1u << 16;
constexpr uint32_t LBO_2K   = (2048u >> 4) << 16;
constexpr uint32_t LBO_512  = (512u >> 4) << 16;
__device__ __forceinline__ uint64_t mk_desc(uint32_t lo, uint32_t hi) { uint64_t d; asm("mov.b64 %0, {%1, %2};" : "=l"(d) : "r"(lo), "r"(hi)); return d; }

__device__ __forceinline__ uint32_t pack_bf16(float lo, float hi) {
  uint32_t r; asm("cvt.rn.bf16x2.f32 %0, %1, %2;" : "=r"(r) : "f"(hi), "f"(lo)); return r;
}
__device__ __forceinline__ float bf_lo(uint32_t v) { return __uint_as_float(v << 16); }
__device__ __forceinline__ float bf_hi(uint32_t v) { return __uint_as_float(v & 0xffff0000u); }
__device__ __forceinline__ float bf_lo_p(uint32_t v) { uint32_t r; asm("prmt.b32 %0, %1, 0, 0x1044;" : "=r"(r) : "r"(v)); return __uint_as_float(r); }
__device__ __forceinline__ float round_bf(float v) { return bf_lo(pack_bf16(v, 0.f)); }
__device__ __forceinline__ float silu_mul(float g, float u, float k, float sd2) {
  float e, r;
  asm("ex2.approx.ftz.f32 %0, %1;" : "=f"(e) : "f"(g * k));
  asm("rcp.approx.ftz.f32 %0, %1;" : "=f"(r) : "f"(fmaf(e, sd2, sd2)));
  return (g * u) * r;
}
__device__ __forceinline__ float silu_mul_v(float g, float u, float k, float sd2) {
  float e, r;
  asm volatile("ex2.approx.ftz.f32 %0, %1;" : "=f"(e) : "f"(g * k));
  asm volatile("rcp.approx.ftz.f32 %0, %1;" : "=f"(r) : "f"(fmaf(e, sd2, sd2)));
  return (g * u) * r;
}
__device__ __forceinline__ int unit_of(int role, int t) {
  const int two_ab = (role & 5) == 0;
  if (t == 0) return role;
  if (t == 1 && two_ab) return 8 + (role >> 1);
  return 9 + 3 * role + (role > 4) + (role > 6) + t - two_ab;
}

struct UnitSrc { const CUtensorMap *m0, *m1; int x0, y0, y1, dx, dy; };
__device__ __forceinline__ UnitSrc unit_src(const Maps& maps, int unit) {
  UnitSrc u;
  const bool ab = unit < 10;
  u.m0 = &maps.dr + (ab ? (unit >= 5) : 2);
  u.m1 = u.m0 + (ab ? 0 : 1);
  u.x0 = ab ? 0 : (unit - 10) * 64;
  u.y0 = ab ? (unit - (unit >= 5) * 5) * 128 : 0;
  u.y1 = u.y0 + (ab ? 64 : 0);
  u.dx = ab ? 64 : 0; u.dy = 64 - u.dx;
  return u;
}

template<int K0, int K1> __device__ __forceinline__ void prefetch_rows(const Params& p) {
  const char* a; uint32_t on;
  asm volatile("{\n.reg .pred p, q;\n.reg .b64 o;\n.reg .u32 r;\n"
               "setp.lt.u32 p, %6, 80;\nselp.b64 %0, %3, %4, p;\n"
               "setp.lt.u32 p, %5, 16;\nselp.b64 %0, %2, %0, p;\nselp.u32 r, 16, 8, p;\n"
               "mad.lo.u32 r, r, %6, %5;\nmul.wide.u32 o, r, 1280;\nadd.u64 %0, %0, o;\n"
               "setp.lt.u32 q, %6, 128;\nsetp.lt.and.u32 p, %5, 24, q;\nselp.u32 %1, 1, 0, p;\n}\n"
               : "=&l"(a), "=r"(on) : "l"(p.pf[0]), "l"(p.pf[1]), "l"(p.pf[2]), "r"(threadIdx.x & 31), "r"(blockIdx.x));
  #pragma unroll
  for (int k = K0; k < K1; k++)
    asm volatile("{\n.reg .pred p;\nsetp.ne.u32 p, %1, 0;\n@p prefetch.global.L2 [%0];\n}\n" :: "l"(a + k * 128), "r"(on));
}

struct Ctx {
  uint32_t sbase, full1, empty1, pub, tab, full2, empty2, flagb, xfull;
  int wg, warp, lane, zero, rank;
  bool elect;
};

struct TokC { float k[8], sd2[8]; };
__device__ __forceinline__ void load_tokc(TokC& t, uint32_t a) {
  #pragma unroll
  for (int e = 0; e < 8; e++)
    asm volatile("ld.shared.v2.f32 {%0, %1}, [%2];" : "=f"(t.k[e]), "=f"(t.sd2[e]) : "r"(a + (e >> 1) * 128 + (e & 1) * 16 + 8) : "memory");
}
struct SumSrc { uint32_t a, stride, sel; };
__device__ __forceinline__ void centre(const Ctx& c, float (&acc)[2][64], const SumSrc& s, uint32_t bar) {
  uint32_t a[4];
  mbar_wait(bar, 0);
  #pragma unroll
  for (int j = 0; j < 4; j++) asm volatile("ld.shared.u32 %0, [%1];" : "=r"(a[j]) : "r"(s.a + ((j >> 1) * 8 + (j & 1)) * s.stride) : "memory");
  #pragma unroll
  for (int j = 0; j < 4; j++) a[j] = __byte_perm(a[j], 0u, s.sel);
  wgmma_fence();
  #pragma unroll
  for (int i = 0; i < 2; i++) wgmma_rs_n128<0>(acc[i], a[2 * i], a[2 * i + 1], 0u, 0u, mk_desc(DBASE + (TAB_OFF >> 4), 128 >> 4), 1);
  wgmma_commit();
  mbar_arrive_if(c.tab + 48, c.lane == 0);
}
template<bool GU, bool FIRST>
__device__ __forceinline__ void stage1_loop(const Ctx& c, float (&acc)[2][64], int it0, bool more, bool hand, int free2) {
  int prev = 0;
  #pragma unroll 1
  for (int kb = 0; kb < 10; kb++) {
    const int it = it0 + kb;
    const int slot = it & 3;
    const uint32_t bx = DBASE + kb * (A_CHUNK >> 4) + LBO_NONE;
    const uint32_t ar = DBASE + slot * 1024 + ((RING1_OFF >> 4) + LBO_NONE);
    const uint32_t rel = c.elect && kb > 0 && (more || kb <= 10 - R1), rel2 = c.elect && free2 == 4 && kb >= 3 && (kb & 1);
    if (FIRST) mbar_wait(c.xfull + 8 * kb, 0);
    mbar_wait(c.full1 + 8 * slot, (it >> 2) & 1);
    if (kb == 9 && hand) named_arrive(1 + (c.wg ^ 1), 256);
    wgmma_fence();
    #pragma unroll
    for (int k = 0; k < 4; k++) {
      #pragma unroll
      for (int i = 0; i < 2; i++) {
        if (GU) wgmma_ss_n128<1, 0, 1>(acc[i], mk_desc(ar + i * 512 + k * 128, HI_SW128), mk_desc(bx + k * 2, HI_SW128), (kb | k) != 0);
        else    wgmma_ss_n128<0, 0, 1>(acc[i], mk_desc(ar + i * 512 + k * 2, HI_SW128), mk_desc(bx + k * 2, HI_SW128), (kb | k) != 0);
      }
      if (k == 0) {
        wgmma_commit();
        wgmma_wait<1>();
        mbar_arrive_cta_if(c.empty1 + 8 * prev, c.rank ^ 1, rel);
        mbar_arrive_if(c.empty1 + 8 * prev, rel);
        wgmma_fence();
      }
      if (GU && (k == 1 || k == 2)) mbar_arrive_cta_if(c.empty2 + 4 * (kb - 3), k - 1, rel2);
    }
    wgmma_commit();
    prev = slot;
  }
  if (!GU) {
    wgmma_wait<0>();
    mbar_arrive_cta_if(c.empty1 + 8 * prev, c.rank ^ 1, c.elect);
    mbar_arrive_if(c.empty1 + 8 * prev, c.elect);
    fence_acc(acc[0]); fence_acc(acc[1]);
  }
}
template<bool GU>
__device__ __forceinline__ void stage1_tail(const Ctx& c, float (&acc)[2][64], int it0, bool more, int free2,
                                            const SumSrc& ss, uint32_t tabbar, TokC& tc, uint32_t tab) {
  centre(c, acc, ss, tabbar);
  if (GU) {
    const int prev = (it0 + 9) & 3;
    load_tokc(tc, tab);
    #pragma unroll 1
    for (int z = c.zero; z < 1; z++) {
      wgmma_wait<1>();
      if (c.elect) {
        if (more) { mbar_arrive_cta(c.empty1 + 8 * prev, c.rank ^ 1); mbar_arrive(c.empty1 + 8 * prev); }
        if (free2 < R2) {
          #pragma unroll
          for (int j = 4; j < R2; j++) { mbar_arrive_cta(c.empty2 + 8 * j, 0); mbar_arrive_cta(c.empty2 + 8 * j, 1); }
          if (free2 == 0) {
            #pragma unroll
            for (int j = 0; j < 4; j++) { mbar_arrive_cta(c.empty2 + 8 * j, 0); mbar_arrive_cta(c.empty2 + 8 * j, 1); }
          }
        }
      }
    }
  }
  wgmma_wait<0>();
  fence_acc(acc[0]); fence_acc(acc[1]);
}
__device__ __forceinline__ void store_ab(const Ctx& c, const float (&acc)[2][64], uint4* dst, uint32_t tab, float scale) {
  uint4 w[16];
  #pragma unroll
  for (int J = 0; J < 4; J++) {
    float rs[8];
    #pragma unroll
    for (int e = 0; e < 8; e++) {
      asm volatile("ld.shared.f32 %0, [%1];" : "=f"(rs[e]) : "r"(tab + J * 512 + (e >> 1) * 128 + (e & 1) * 16 + 8) : "memory");
      rs[e] *= scale;
    }
    #pragma unroll
    for (int i = 0; i < 2; i++)
      #pragma unroll
      for (int hf = 0; hf < 2; hf++) {
        const int r = 16 * J + 2 * hf;
        w[4 * J + 2 * i + hf] = make_uint4(pack_bf16(acc[i][r] * rs[0], acc[i][r + 1] * rs[1]), pack_bf16(acc[i][r + 4] * rs[2], acc[i][r + 5] * rs[3]),
                                           pack_bf16(acc[i][r + 8] * rs[4], acc[i][r + 9] * rs[5]), pack_bf16(acc[i][r + 12] * rs[6], acc[i][r + 13] * rs[7]));
        dst[(i * 8 + hf) * S_ + J * 32] = w[4 * J + 2 * i + hf];
        if (i + hf + J < 5) pace<50>();
      }
  }
  if (c.zero) {
    #pragma unroll
    for (int j = 0; j < 16; j++) dst[j] = w[j];
  }
}
__device__ __forceinline__ void store_h(const Ctx& c, const float (&acc)[2][64], uint4* dst, uint32_t tab, TokC (&tc)[2]) {
  uint4 w[8];
  #pragma unroll
  for (int sl = 0; sl < 8; sl++) {
    const int J = sl >> 1, hf = sl & 1, r = 16 * J + 2 * hf;
    const TokC& t = tc[J & 1];
    if (hf == 0 && J < 3) load_tokc(tc[(J + 1) & 1], tab + (J + 1) * 512);
    w[sl] = make_uint4(0u, 0u, 0u, 0u);
    #pragma unroll 1
    for (int z = c.zero; z < 1; z++) {
      uint32_t v[4];
      #pragma unroll
      for (int b = 0; b < 4; b++)
        v[b] = pack_bf16(silu_mul_v(acc[0][r + 4 * b], acc[1][r + 4 * b], t.k[2 * b], t.sd2[2 * b]),
                         silu_mul_v(acc[0][r + 4 * b + 1], acc[1][r + 4 * b + 1], t.k[2 * b + 1], t.sd2[2 * b + 1]));
      w[sl] = make_uint4(v[0], v[1], v[2], v[3]);
      dst[hf * S_ + J * 32] = w[sl];
    }
  }
  if (c.zero < 0) {
    #pragma unroll
    for (int j = 0; j < 8; j++) dst[j] = w[j];
  }
}
__device__ __forceinline__ int sum_unit(int n) { return n < 32 ? unit_of(2 * (n & 3) + (~n >> 2 & 1), n >> 3) : n < 36 ? unit_of(2 * (n - 32), 4) : 36; }
constexpr int RS = 7;
template<bool GU>
__device__ __forceinline__ void sum_mma(const Ctx& c, float (&d)[4], int& slot, int& ph) {
  int prev = 0;
  const uint32_t bar = c.full2 + c.wg * (16 * RS);
  #pragma unroll 1
  for (int kb = 0; kb < 5; kb++) {
    const uint32_t ar = DBASE + (c.wg * RS + slot) * 1024 + LBO_NONE, ones = DBASE + (TAB_OFF >> 4) + LBO_NONE;
    mbar_wait(bar + 8 * slot, ph);
    wgmma_fence();
    #pragma unroll
    for (int k = 0; k < 8; k++) wgmma_ss_n8<GU>(d, mk_desc(ar + (GU ? k * 128 : (k >> 2) * 512 + (k & 3) * 2), HI_SW128), mk_desc(ones, HI_SW128), (kb | k) != 0);
    wgmma_commit();
    wgmma_wait<1>();
    mbar_arrive_if(bar + 8 * (RS + prev), c.elect && kb > 0);
    prev = slot;
    if (++slot == RS) { slot = 0; ph ^= 1; }
  }
  wgmma_wait<0>();
  mbar_arrive_if(bar + 8 * (RS + prev), c.elect);
  fence_acc(d);
}
template<int W>
__device__ __forceinline__ void sum_loads(const Ctx& c, const Maps& maps) {
  const uint32_t bar = c.full2 + W * (16 * RS);
  int slot = 0, ph = 1;
  #pragma unroll 1
  for (int n = blockIdx.x - 128; n < 37; n += 4) {
    const UnitSrc u = unit_src(maps, sum_unit(n));
    const CUtensorMap* m = W ? u.m1 : u.m0;
    int x = u.x0, y = W ? u.y1 : u.y0;
    #pragma unroll 1
    for (int kb = 0; kb < 5; kb++) {
      const uint32_t full = bar + 8 * slot, dst = c.sbase + (W * RS + slot) * 16384;
      mbar_wait(bar + 8 * (RS + slot), ph);
      mbar_expect_tx(full, 16384);
      tma_load(dst, m, x, y, full);
      tma_load(dst + 8192, m, x + u.dx, y + u.dy, full);
      x += 2 * u.dx; y += 2 * u.dy;
      if (++slot == RS) { slot = 0; ph ^= 1; }
    }
  }
}
__device__ __forceinline__ void write_table(const Ctx& c, const uint4& st, uint32_t bar) {
  const uint32_t sv[4] = {st.x, st.y, st.z, st.w};
  #pragma unroll
  for (int e = 0; e < 4; e++) {
    const uint32_t a = c.sbase + TAB_OFF + (c.lane + 32 * e) * 16;
    const float sd = bf_hi(sv[e]);
    float r;
    asm("rcp.approx.ftz.f32 %0, %1;" : "=f"(r) : "f"(sd));
    asm volatile("st.shared.u32 [%0], %1;" :: "r"(a), "r"(__byte_perm(sv[e], 0u, 0x1010)) : "memory");
    asm volatile("st.shared.u16 [%0], %1;" :: "r"(a + 4), "h"((uint16_t)sv[e]) : "memory");
    asm volatile("st.shared.v2.u32 [%0], {%1, %2};" :: "r"(a + 8), "r"(__float_as_uint(r * -1.4426950408889634f) & ~0x80u), "r"(__float_as_uint(sd * sd)) : "memory");
  }
  asm volatile("fence.proxy.async.shared::cta;" ::: "memory");
  mbar_arrive(bar);
}
__device__ __forceinline__ void publish(const Ctx& c, int t) {
  __syncwarp();
  if (c.lane == 0) mbar_arrive(c.pub + 8 * t);
}
__device__ __forceinline__ void release2(const Ctx& c, int slot) {
  if (c.elect) { mbar_arrive_cta(c.empty2 + 8 * slot, 0); mbar_arrive_cta(c.empty2 + 8 * slot, 1); }
}
template<bool DPART>
__device__ __forceinline__ void stage2_kb(const Ctx& c, float (&acc)[80], int slot, int ph, int prev, bool rel) {
  const uint32_t sa = DBASE + slot * (SLOT2 >> 4) + c.wg * 512 + (DPART ? LBO_512 : LBO_NONE), sb = DBASE + slot * (SLOT2 >> 4) + (1024 + (DPART ? LBO_2K : LBO_NONE));
  mbar_wait(c.full2 + 8 * slot, ph);
  wgmma_fence();
  #pragma unroll
  for (int k = 0; k < 4; k++) {
    if (DPART) wgmma_ss_n160<1, 1, 1>(acc, mk_desc(sa + k * 128, HI_SW64K), mk_desc(sb + (k >> 1) * 640 + (k & 1) * 64, HI_SW64), 1);
    else       wgmma_ss_n160<0, 0, 1>(acc, mk_desc(sa + k * 2, HI_SW128), mk_desc(sb + (k >> 1) * 32 + (k & 1) * 2, HI_SW64K), 1);
    if (k == 0) {
      wgmma_commit();
      wgmma_wait<1>();
      if (rel) release2(c, prev);
      wgmma_fence();
    }
  }
  wgmma_commit();
}

struct OutAddr { uint32_t sw, lf, lh; char *gf, *gh; };
__device__ __forceinline__ void fin_st(const float (&acc)[80], const OutAddr& o, int hf, int j0, int j1) {
  #pragma unroll
  for (int jj = j0; jj < j1; jj++) {
    asm volatile("stmatrix.sync.aligned.m8n8.x4.shared.b16 [%0], {%1, %2, %3, %4};" :: "r"(o.sw + hf * (8 * 336) + jj * 64),
                 "r"(pack_bf16(acc[16 * jj + 2 * hf], acc[16 * jj + 2 * hf + 1])), "r"(pack_bf16(acc[16 * jj + 4 + 2 * hf], acc[16 * jj + 5 + 2 * hf])),
                 "r"(pack_bf16(acc[16 * jj + 8 + 2 * hf], acc[16 * jj + 9 + 2 * hf])), "r"(pack_bf16(acc[16 * jj + 12 + 2 * hf], acc[16 * jj + 13 + 2 * hf])) : "memory");
  }
}
__device__ __forceinline__ void fin_ld(uint4& v, const OutAddr& o, int hf, int i) {
  const uint32_t a = (i < 4 ? o.lf + (i >> 1) * (4 * 336) + (i & 1) * 128 : o.lh) + hf * (8 * 336);
  asm volatile("ld.shared.v4.u32 {%0, %1, %2, %3}, [%4];" : "=r"(v.x), "=r"(v.y), "=r"(v.z), "=r"(v.w) : "r"(a) : "memory");
}
__device__ __forceinline__ void fin_red(const uint4& v, const OutAddr& o, int hf, int i) {
  char* g = (i < 4 ? o.gf + (i >> 1) * (4 * D_ * 2) + (i & 1) * 128 : o.gh) + hf * (8 * D_ * 2);
  asm volatile("red.global.add.noftz.v4.bf16x2 [%0], {%1, %2, %3, %4};" :: "l"(g), "r"(v.x), "r"(v.y), "r"(v.z), "r"(v.w) : "memory");
}
__device__ __forceinline__ void stage2_finish(const float (&acc)[80], const OutAddr& o) {
  uint4 v[2][5];
  #pragma unroll
  for (int hf = 0; hf < 2; hf++) {
    fin_st(acc, o, hf, 0, 3);
    __syncwarp();
    fin_ld(v[hf][0], o, hf, 0); fin_ld(v[hf][2], o, hf, 2);
    fin_st(acc, o, hf, 3, 5);
    fin_red(v[hf][0], o, hf, 0); fin_red(v[hf][2], o, hf, 2);
    __syncwarp();
    fin_ld(v[hf][1], o, hf, 1); fin_ld(v[hf][3], o, hf, 3); fin_ld(v[hf][4], o, hf, 4);
    fin_red(v[hf][1], o, hf, 1); fin_red(v[hf][3], o, hf, 3); fin_red(v[hf][4], o, hf, 4);
  }
}

__global__ void __cluster_dims__(2, 1, 1) __launch_bounds__(384, 1)
fused_kernel(const __grid_constant__ Params p, const __grid_constant__ Maps maps) {
  extern __shared__ __align__(1024) uint8_t smem_raw[];
  if (threadIdx.x >= 352) {
    prefetch_rows<0, 2>(p);
  } else if (threadIdx.x >= 320) {
    prefetch_map(&maps.x); prefetch_map(&maps.dr); prefetch_map(&maps.di);
  }
  const int cl = blockIdx.x >> 1, rank = blockIdx.x & 1;
  const bool extra = cl >= 64;
  int kh, nt, grp;
  {
    const int a = cl - 4, b = cl - 36, q = (b * 37) >> 8;
    const int half = (unsigned)a >= 32u;
    const int pos = b >= 0 ? 1 + b - 7 * q : a >= 0 ? a & 7 : 0;
    nt = (b >= 0 ? q : a >= 0 ? a >> 3 : cl) & 3;
    kh = pos >> 2; grp = (pos & 3) * 2 + half;
  }
  const int mb2 = grp * 2 + rank;
  const int role = kh + 2 * nt;
  const int mb1 = extra ? (cl - 64) * 8 + rank : mb2;
  Ctx c;
  c.sbase = __shfl_sync(0xffffffffu, smem_u32(smem_raw), 0);
  c.zero = __shfl_sync(0xffffffffu, threadIdx.x >> 10, 0);
  c.full1 = c.sbase + BAR_OFF; c.empty1 = c.full1 + 8 * R1; c.pub = c.empty1 + 8 * R1; c.tab = c.pub + 8 * 5;
  c.full2 = c.tab + 56; c.flagb = c.full2 + 8 * R2; c.xfull = c.flagb + 8 * 4; c.empty2 = c.xfull + 8 * 10;
  c.wg = __shfl_sync(0xffffffffu, threadIdx.x >> 7, 0);
  c.warp = __shfl_sync(0xffffffffu, (threadIdx.x >> 5) & 3, 0);
  c.lane = threadIdx.x & 31;
  c.rank = rank;
  c.elect = (threadIdx.x & 127) == 0;

  int wlo = c.warp & 1, whi = c.warp >> 1;
  asm volatile("" : "+r"(wlo)); asm volatile("" : "+r"(whi));
  const bool w0 = !whi && !wlo, w1 = !whi && wlo, w2 = whi && !wlo;
  const bool early = c.wg == 2 && w0 && !extra;
  if (c.wg == 2) reg_dealloc<40>();
  const CUtensorMap* md = &maps.dr + (role >= 5);
  const int yd = (role - (role >= 5) * 5) * 128;
  if (early) {
    if (elect_one()) {
      mbar_init(c.xfull, 1); mbar_init(c.full1, 1);
      asm volatile("fence.mbarrier_init.release.cluster;" ::: "memory");
      mbar_expect_tx(c.xfull, A_CHUNK); mbar_expect_tx(c.full1, 16384);
      tma_load_5d(c.sbase, &maps.x, 0, mb2 * 4, c.xfull);
      tma_load(c.sbase + RING1_OFF, md, 0, yd, c.full1);
      tma_load(c.sbase + RING1_OFF + 8192, md, 0, yd + 64, c.full1);
      #pragma unroll
      for (int i = 1; i < XE; i++) mbar_init(c.xfull + 8 * i, 1);
      #pragma unroll
      for (int i = 1; i < R1; i++) mbar_init(c.full1 + 8 * i, 1);
      asm volatile("fence.mbarrier_init.release.cluster;" ::: "memory");
    }
    __syncwarp();
    asm volatile("barrier.cluster.arrive.relaxed.aligned;" ::: "memory");
    if (elect_one()) {
      #pragma unroll
      for (int kb = 1; kb < R1; kb++) {
        if (kb < XE) { mbar_expect_tx(c.xfull + 8 * kb, A_CHUNK); tma_load_5d(c.sbase + kb * A_CHUNK, &maps.x, kb * 64, mb2 * 4, c.xfull + 8 * kb); }
        mbar_expect_tx(c.full1 + 8 * kb, 16384);
        tma_load(c.sbase + RING1_OFF + kb * 16384, md, kb * 64, yd, c.full1 + 8 * kb);
        tma_load(c.sbase + RING1_OFF + kb * 16384 + 8192, md, kb * 64, yd + 64, c.full1 + 8 * kb);
      }
    }
    __syncwarp();
  }
  const int nT = extra ? 4 : 5 - kh;
  const int nC = kh ? NC1 : 64 - NC1, c0 = kh ? 0 : NC1, nD = kh ? ND1 : 27 - ND1, d0 = kh ? 0 : ND1;
  const int n2 = nC + nD;

  if (c.wg == 2) {
    if (!early) {
      if (whi && wlo) prefetch_rows<2, 4>(p);
      if (c.lane == 0) {
        if (w1) {
          #pragma unroll
          for (int i = XE; i < 10; i++) mbar_init(c.xfull + 8 * i, 1);
          #pragma unroll
          for (int i = 0; i < R1; i++) mbar_init(c.empty1 + 8 * i, 2);
        } else if (w2) {
          #pragma unroll
          for (int i = 0; i < R2 + 4; i++) mbar_init(c.full2 + 8 * i, 1);
          mbar_init(c.tab + 40, 4); mbar_init(c.tab + 48, 4);
          #pragma unroll
          for (int i = 0; i < 5; i++) mbar_init(c.pub + 8 * i, 4);
        } else if (!w0) {
          #pragma unroll
          for (int i = 0; i < 5; i++) mbar_init(c.tab + 8 * i, i == 0 ? 64 : 32);
          #pragma unroll
          for (int i = 0; i < R2 + 2; i++) mbar_init(c.empty2 + 8 * i, extra ? 1 : 4);
        } else {
          #pragma unroll
          for (int i = 0; i < XE; i++) mbar_init(c.xfull + 8 * i, 1);
          #pragma unroll
          for (int i = 0; i < R1; i++) mbar_init(c.full1 + 8 * i, 1);
        }
        asm volatile("fence.mbarrier_init.release.cluster;" ::: "memory");
      }
      __syncwarp();
      asm volatile("barrier.cluster.arrive.relaxed.aligned;" ::: "memory");
    }
    if (w1 && c.lane == 0 && !extra) {
      #pragma unroll
      for (int i = XE; i < 10; i++) mbar_expect_tx(c.xfull + 8 * i, A_CHUNK);
    }
    __syncwarp();
    asm volatile("barrier.cluster.wait.acquire.aligned;" ::: "memory");
    if (w0) {
      if (c.lane == 0) {
        if ((c.sbase & 0x3FFFFu) != 0x400u) asm volatile("trap;");
        prefetch_map(&maps.wg); prefetch_map(&maps.wu); prefetch_map(&maps.di); prefetch_map(&maps.dr); prefetch_map(&maps.x);
        if (extra) { sum_loads<0>(c, maps); mbar_wait(c.tab + 40, 0); }
        const CUtensorMap *m, *mn = nullptr;
        int x, y, dx, xn = 0, yn = 0, dxn = 0, kb = extra ? 0 : R1, t = 0;
        {
          const UnitSrc u = unit_src(maps, extra ? 36 : role);
          m = rank ? u.m1 : u.m0; dx = u.dx; x = u.x0 + kb * dx; y = (rank ? u.y1 : u.y0) + kb * (64 - dx);
        }
        #pragma unroll 1
        for (int it = kb; it < nT * 10; it++) {
          const int slot = it & 3;
          const uint32_t full = c.full1 + 8 * slot;
          const uint32_t dst = c.sbase + RING1_OFF + slot * 16384 + rank * 8192;
          mbar_wait(full, ((it >> 2) & 1) ^ 1);
          mbar_expect_tx(full, extra ? 32768 : 16384);
          mbar_wait(c.empty1 + 8 * slot, ((it >> 2) & 1) ^ 1);
          tma_load_mc(dst, m, x, y, full);
          if (extra) tma_load_5d(c.sbase + kb * A_CHUNK, &maps.x, kb * 64, (mb1 + 2 * t) * 4, full);
          x += dx; y += 64 - dx;
          if (kb == 5) {
            const UnitSrc u = unit_src(maps, extra ? 36 : unit_of(role, t + 1));
            mn = rank ? u.m1 : u.m0; dxn = u.dx; xn = u.x0; yn = rank ? u.y1 : u.y0;
          }
          if (++kb == 10) { kb = 0; t++; m = mn; x = xn; y = yn; dx = dxn; }
        }
      }
    } else if (w1) {
      if (extra) {
        if (c.lane == 0) sum_loads<1>(c, maps);
      } else if (c.lane == 0) {
        #pragma unroll 1
        for (int i = XE; i < 10; i++) {
          mbar_wait(c.xfull + 8 * (i - XE), 0);
          tma_load_5d(c.sbase + i * A_CHUNK, &maps.x, i * 64, mb1 * 4, c.xfull + 8 * i);
        }
        prefetch_map(&maps.cr); prefetch_map(&maps.ci); prefetch_map(&maps.ab); prefetch_map(&maps.h); prefetch_map(&maps.wd);
        uint64_t pol;
        asm volatile("createpolicy.fractional.L2::evict_first.b64 %0, 1.0;" : "=l"(pol));
        int slot = 0, ph = 0;
        #pragma unroll 1
        for (int i = 0; i < n2; i++) {
          const uint32_t full = c.full2 + 8 * slot;
          const uint32_t dst = c.sbase + slot * SLOT2;
          mbar_wait(full, ph ^ 1);
          mbar_expect_tx(full, SLOT2);
          mbar_wait(c.empty2 + 8 * slot, ph);
          if (i == 0) { mbar_wait(c.flagb, 0); fence_proxy_async_global(); }
          if (c0 + i == max(c0, 32)) { mbar_wait(c.flagb + 24, 0); fence_proxy_async_global(); }
          if (i < nC) {
            const int kc = c0 + i;
            const int im = kc >= 32;
            const int kk = (kc & 31) * 64;
            tma_load_stream(dst, im ? &maps.ci : &maps.cr, kk, mb2 * 128, full, pol);
            tma_load_mc(dst + 16384 + rank * 10240, &maps.ab, kk * 4, im * 80 + nt * 20 + rank * 10, full);
          } else {
            const int kd = d0 + i - nC;
            tma_load_3d_mc(dst + 16384 + rank * 10240, &maps.wd, kd * 64 + rank * 32, nt * 5, full);
            if (i == nC) { mbar_wait(c.flagb + 8, 0); fence_proxy_async_global(); }
            if (kd == 26) { mbar_wait(c.flagb + 16, 0); fence_proxy_async_global(); }
            tma_load_3d(dst, &maps.h, kd * 8, mb2 * 2, full);
          }
          if (++slot == R2) { slot = 0; ph ^= 1; }
        }
      }
    } else if (w2) {
      const uint32_t tag = ld_relaxed(&p.cnt[CNT_EPOCH * 32]) + 1;
      if (!extra) {
        __nanosleep(1500);
        {
          const int unit = unit_of(role, 1);
          #pragma unroll 1
          for (int j = c.lane; j < 80; j += 32) {
            const char* a = unit < 10 ? p.pf[2] + (unit * 128 + 16 + mb1 * 8 + j / 10) * (D_ * 2) + (j % 10) * 128
                                      : p.pf[3 + (j & 1)] + (mb1 * 40 + (j >> 1)) * (F_ * 2) + (unit - 10) * 128;
            asm volatile("prefetch.global.L2 [%0];" :: "l"(a));
          }
        }
        __syncwarp();
        named_sync(3, 128 + 32);
        __nanosleep(250);
      } else {
        mbar_wait(c.tab + 40, 0);
      }
      write_table(c, ll_load4(p.ll + mb1 * 128 + c.lane, tag), c.tab);
      __syncwarp();
      #pragma unroll 1
      for (int t = 0; t < nT; t++) {
        uint4 st;
        if (extra && t < 3) st = ll_load4(p.ll + (mb1 + 2 * t + 2) * 128 + c.lane, tag);
        mbar_wait(c.pub + 8 * t, 0);
        if (extra && t < 3) write_table(c, st, c.tab + 8 * t + 8);
        __syncwarp();
        if (c.lane == 0) {
          const int unit = unit_of(role, t);
          red_release(&p.cnt[(extra ? CNT_HX + mb1 + 2 * t : unit < 5 ? CNT_A : unit < 10 ? CNT_B : CNT_H + mb1) * 32]);
        }
        __syncwarp();
      }
      if (!extra) {
        #pragma unroll 1
        for (int i = 0; i < 5; i++) {
          if (c.lane < 27) asm volatile("prefetch.global.L2 [%0];" :: "l"((const char*)p.wd + blockIdx.x * (D_ * F_ * 2 / 128) + (i * 27 + c.lane) * 128));
          __nanosleep(600);
        }
      }
    } else {
      prefetch_rows<4, 10>(p);
      const uint32_t tag = ld_relaxed(&p.cnt[CNT_EPOCH * 32]) + 1;
      if (extra) mbar_wait(c.tab + 40, 0);
      else __nanosleep(2000);
      #pragma unroll 1
      for (int t = 0; t < (extra ? 1 : nT); t++) {
        const uint4 sm = ll_load4(p.ll + S_ + (extra ? 36 : unit_of(role, t)) * 128 + c.lane, tag);
        const uint32_t sw[4] = {sm.x, sm.y, sm.z, sm.w};
        uint32_t hm[4], lo[4];
        #pragma unroll
        for (int e = 0; e < 4; e++) {
          const float s = __uint_as_float(sw[e]), hi = round_bf(s);
          hm[e] = pack_bf16(hi, s - hi);
          lo[e] = pack_bf16(s - hi - bf_hi(hm[e]), 0.f);
        }
        if (t > 0) mbar_wait(c.tab + 48, (t - 1) & 1);
        if (t == nT - 2 && c.lane == 0) {
          #pragma unroll 1
          for (int i = role * 5; i < role * 5 + 5; i++) {
            asm volatile("cp.async.bulk.tensor.5d.global.shared::cta.bulk_group [%0, {%2, %4, %4, %4, %3}], [%1];"
              :: "l"(&maps.o), "r"(c.sbase + i * 4096), "r"((i >> 2) * 64), "r"(mb1 * 4 + (i & 3)), "r"(0) : "memory");
            pace<200>();
          }
          asm volatile("cp.async.bulk.commit_group;" ::: "memory");
          asm volatile("cp.async.bulk.wait_group.read 0;" ::: "memory");
        }
        if (t == nT - 1 && c.lane == 0) {
          asm volatile("cp.async.bulk.wait_group 0;" ::: "memory");
          fence_proxy_async_global();
        }
        __syncwarp();
        #pragma unroll
        for (int e = 0; e < 4; e++) asm volatile("st.shared.u16 [%0], %1;" :: "r"(c.sbase + TAB_OFF + (c.lane + 32 * e) * 16 + 6), "h"((uint16_t)lo[e]) : "memory");
        #pragma unroll
        for (int e = 0; e < 4; e++) asm volatile("st.shared.u32 [%0], %1;" :: "r"(c.sbase + SUM_OFF + (c.lane + 32 * e) * 4), "r"(hm[e]) : "memory");
        if (t == 0) asm volatile("fence.proxy.async.shared::cta;" ::: "memory");
        mbar_arrive(c.tab + 8 * t);
      }
      if (!extra && c.lane == 0) {
        wait_counter<300>(&p.cnt[CNT_A * 32], 80);           mbar_arrive(c.flagb);
        wait_counter<300>(&p.cnt[CNT_B * 32], 80);           mbar_arrive(c.flagb + 24);
        wait_counter<500>(&p.cnt[(CNT_H + mb2) * 32], 26);   mbar_arrive(c.flagb + 8);
        wait_counter<500>(&p.cnt[(CNT_HX + mb2) * 32], 1);   mbar_arrive(c.flagb + 16);
        if (atomicAdd(&p.cnt[CNT_DONE * 32], 1u) == 127u) {
          for (int i = 0; i < CNT_TOTAL; i++) p.cnt[i * 32] = 0;
          p.cnt[CNT_EPOCH * 32] = tag;
        }
      }
    }
  } else {
    asm volatile("barrier.cluster.arrive.relaxed.aligned;" ::: "memory");
    reg_alloc<232>();
    float acc1[2][64];
    const bool first = c.wg == 0 && !extra;
    if (first) {
      asm volatile("barrier.cluster.wait.acquire.aligned;" ::: "memory");
      stage1_loop<false, true>(c, acc1, 0, true, true, R2);
    }
    const int rl = c.warp * 16 + (c.lane >> 2);
    OutAddr o;
    {
      const uint32_t stg = c.sbase + ((n2 + c.warp) % R2) * SLOT2 + c.wg * 8192;
      const int rf = c.lane >> 3, cf = (nt & 1) * 64 + (c.lane & 7) * 16;
      const int rh = (c.lane >> 3) + (c.lane & 4), ch = ((nt & 1) ^ 1) * 256 + (c.lane & 3) * 16;
      const uint32_t ob = ((mb2 * 128 + c.wg * 64 + c.warp * 16) * D_ + nt * 160) * 2;
      o.sw = stg + (c.lane & 7) * 336 + (c.lane >> 3) * 16;
      o.lf = stg + rf * 336 + cf; o.lh = stg + rh * 336 + ch;
      o.gf = reinterpret_cast<char*>(p.out) + ob + rf * (D_ * 2) + cf; o.gh = reinterpret_cast<char*>(p.out) + ob + rh * (D_ * 2) + ch;
      asm volatile("" : "+r"(o.sw), "+r"(o.lf), "+r"(o.lh), "+l"(o.gf), "+l"(o.gh));
    }
    uint32_t tab = c.sbase + TAB_OFF + (c.lane & 3) * 32;
    SumSrc ss;
    ss.a = c.sbase + ((c.lane & 1) ? TAB_OFF + rl * 16 + 4 : SUM_OFF + rl * 4);
    ss.stride = (c.lane & 1) ? 128 : 32;
    ss.sel = (c.lane & 2) ? 0x4444 : (c.lane & 1) ? 0x4432 : 0x3210;
    int lo = c.warp * 2 * S_ + (c.lane ^ (c.lane >> 3));
    asm volatile("" : "+r"(tab), "+r"(lo), "+r"(ss.a), "+r"(ss.stride), "+r"(ss.sel));
    if (!first) asm volatile("barrier.cluster.wait.acquire.aligned;" ::: "memory");
    if (extra) {
      const uint32_t epoch = ld_relaxed(&p.cnt[CNT_EPOCH * 32 + (threadIdx.x >> 10)]);
      asm volatile("st.shared.u32 [%0], %1;" :: "r"(c.sbase + TAB_OFF + threadIdx.x * 4), "r"(0x3f803f80u) : "memory");
      asm volatile("fence.proxy.async.shared::cta;" ::: "memory");
      named_sync(3, 256);
      int slot = 0, ph = 0;
      #pragma unroll 1
      for (int n = blockIdx.x - 128; n < 37; n += 4) {
        const int unit = sum_unit(n);
        float d[4];
        if (unit < 10) sum_mma<false>(c, d, slot, ph);
        else           sum_mma<true>(c, d, slot, ph);
        if ((c.lane & 3) == 0) {
          unsigned long long* dst = p.ll + S_ + unit * 128 + c.wg * 64 + rl;
          ll_store(dst, __float_as_uint(d[0]), epoch); ll_store(dst + 8, __float_as_uint(d[2]), epoch);
        }
        __syncwarp();
      }
      if (c.elect) { mbar_arrive_cta(c.tab + 40, 0); mbar_arrive_cta(c.tab + 40, 1); }
    } else if (c.wg == 1) {
      const uint32_t epoch = ld_relaxed(&p.cnt[CNT_EPOCH * 32 + (threadIdx.x >> 10)]);
      const int row = role * 16 + ((threadIdx.x >> 3) & 15);
      const uint32_t xa = c.sbase + row * 128 + (((c.lane ^ row) & 7) << 4);
      float sh = 0.f, s = 0.f, q = 0.f;
      #pragma unroll 1
      for (int i = 0; i < 10; i++) {
        uint32_t w[4];
        mbar_wait(c.xfull + 8 * i, 0);
        asm volatile("ld.shared.v4.u32 {%0, %1, %2, %3}, [%4];" : "=r"(w[0]), "=r"(w[1]), "=r"(w[2]), "=r"(w[3]) : "r"(xa + i * A_CHUNK) : "memory");
        if (i == 0) sh = bf_lo(__shfl_sync(0xffffffffu, w[0], c.lane & 24));
        #pragma unroll
        for (int j = 0; j < 4; j++) { const float a = bf_lo_p(w[j]) - sh, b = bf_hi(w[j]) - sh; s += a; q = fmaf(a, a, q); s += b; q = fmaf(b, b, q); }
      }
      #pragma unroll
      for (int o = 1; o < 8; o <<= 1) { s += __shfl_xor_sync(0xffffffffu, s, o); q += __shfl_xor_sync(0xffffffffu, q, o); }
      const float dm = s * (1.0f / D_);
      const float var = fmaxf(fmaf(-dm, dm, q * (1.0f / D_)), 0.f);
      float sd;
      asm("sqrt.approx.ftz.f32 %0, %1;" : "=f"(sd) : "f"(round_bf(round_bf(var) + 1e-5f)));
      if ((c.lane & 7) == 0) ll_store(p.ll + mb1 * 128 + row, pack_bf16(-(sh + dm), sd), epoch);
      named_arrive(3, 128 + 32);
    }

    TokC tc[2];
    int t = c.wg;
    #pragma unroll 1
    for (; t < nT; t += 2) {
      const int unit = extra ? 36 : unit_of(role, t);
      const int col = (extra ? mb1 + 2 * t : mb1) * 128 + lo;
      if (t > 0) named_sync(1 + c.wg, 256);
      const bool more = t < nT - 1;
      if (unit < 10) {
        if (t > 0) stage1_loop<false, false>(c, acc1, t * 10, true, true, R2);
        stage1_tail<false>(c, acc1, t * 10, true, R2, ss, c.tab + 8 * t, tc[0], tab);
        store_ab(c, acc1, reinterpret_cast<uint4*>(p.abT) + unit * 16 * S_ + col, tab, unit < 5 ? -0.6931471805599453f : 0.6931471805599453f);
      } else {
        const int free2 = extra ? R2 : !more ? 4 : t == nT - 2 ? 0 : R2;
        stage1_loop<true, false>(c, acc1, t * 10, more, more || !extra, free2);
        stage1_tail<true>(c, acc1, t * 10, more, free2, ss, c.tab + 8 * t, tc[0], tab);
        if (!more && !extra) break;
        store_h(c, acc1, reinterpret_cast<uint4*>(p.hT) + (unit - 10) * 8 * S_ + col, tab, tc);
      }
      publish(c, t);
    }

    if (!extra) {
      float acc[80];
      int i0 = 0;
      if (t < nT) {
        const int unit = unit_of(role, t);
        uint32_t gu[2][32];
        #pragma unroll
        for (int r = 0; r < 32; r++) { gu[0][r] = pack_bf16(acc1[0][2 * r], acc1[0][2 * r + 1]); gu[1][r] = pack_bf16(acc1[1][2 * r], acc1[1][2 * r + 1]); }
        #pragma unroll
        for (int r = 0; r < 80; r++) acc[r] = 0.f;
        uint4* dst = reinterpret_cast<uint4*>(p.hT) + (unit - 10) * 8 * S_ + mb1 * 128 + lo;
        uint4 w[8];
        #pragma unroll
        for (int i = 0; i < 8; i++) {
          const int J = i >> 1, hf = i & 1;
          const TokC& k = tc[J & 1];
          if (hf == 1 && J < 3) load_tokc(tc[(J + 1) & 1], tab + (J + 1) * 512);
          stage2_kb<false>(c, acc, i % R2, i / R2, (i + R2 - 1) % R2, i > 0);
          uint32_t v[4];
          #pragma unroll
          for (int b = 0; b < 4; b++) {
            const int r = 8 * J + 2 * b + hf;
            v[b] = pack_bf16(silu_mul(bf_lo(gu[0][r]), bf_lo(gu[1][r]), k.k[2 * b], k.sd2[2 * b]), silu_mul(bf_hi(gu[0][r]), bf_hi(gu[1][r]), k.k[2 * b + 1], k.sd2[2 * b + 1]));
          }
          w[i] = make_uint4(v[0], v[1], v[2], v[3]);
          dst[hf * S_ + J * 32] = w[i];
        }
        if (c.zero) {
          #pragma unroll
          for (int j = 0; j < 8; j++) dst[j] = w[j];
        }
        publish(c, t);
        wgmma_wait<0>();
        fence_acc(acc);
        i0 = 8;
      }
      if (i0 == 0) {
        #pragma unroll
        for (int r = 0; r < 80; r++) acc[r] = 0.f;
        named_sync(1 + c.wg, 256);
      }
      int slot = i0 % R2, ph = i0 / R2, prev = (i0 + R2 - 1) % R2;
      #pragma unroll 1
      for (int i = i0; i < nC; i++) {
        stage2_kb<false>(c, acc, slot, ph, prev, i > 0);
        prev = slot;
        if (++slot == R2) { slot = 0; ph ^= 1; }
      }
      const bool lead = c.wg != kh;
      #pragma unroll 1
      for (int i = nC; i < n2; i++) {
        if (i == n2 - R2 && lead) {
          wgmma_wait<0>();
          release2(c, prev);
          named_sync(4, 256);
        }
        stage2_kb<true>(c, acc, slot, ph, prev, i - 1 < n2 - R2 && !(lead && i == n2 - R2));
        prev = slot;
        if (++slot == R2) { slot = 0; ph ^= 1; }
      }
      if (!lead) named_arrive(4, 256);
      wgmma_wait<0>();
      fence_acc(acc);
      stage2_finish(acc, o);
    }
  }
}

typedef CUresult (*PFN_encodeTiled)(CUtensorMap*, CUtensorMapDataType, cuuint32_t, void*, const cuuint64_t*, const cuuint64_t*,
                                    const cuuint32_t*, const cuuint32_t*, CUtensorMapInterleave, CUtensorMapSwizzle,
                                    CUtensorMapL2promotion, CUtensorMapFloatOOBfill);

void make_map(PFN_encodeTiled enc, CUtensorMap* m, const void* ptr, uint64_t rows, uint64_t cols, uint32_t box_rows, uint32_t box_cols, CUtensorMapSwizzle sw) {
  cuuint64_t dims[2] = {cols, rows};
  cuuint64_t strides[1] = {cols * 2};
  cuuint32_t box[2] = {box_cols, box_rows};
  cuuint32_t es[2] = {1, 1};
  enc(m, CU_TENSOR_MAP_DATA_TYPE_BFLOAT16, 2, const_cast<void*>(ptr), dims, strides, box, es, CU_TENSOR_MAP_INTERLEAVE_NONE, sw,
      CU_TENSOR_MAP_L2_PROMOTION_L2_256B, CU_TENSOR_MAP_FLOAT_OOB_FILL_NONE);
}
void make_map3(PFN_encodeTiled enc, CUtensorMap* m, const void* ptr, uint64_t rows, uint64_t cols, uint32_t box_rows, uint32_t box_cols, uint32_t nblk, CUtensorMapSwizzle sw) {
  cuuint64_t dims[3] = {box_cols, rows, cols / box_cols};
  cuuint64_t strides[2] = {cols * 2, (cuuint64_t)box_cols * 2};
  cuuint32_t box[3] = {box_cols, box_rows, nblk};
  cuuint32_t es[3] = {1, 1, 1};
  enc(m, CU_TENSOR_MAP_DATA_TYPE_BFLOAT16, 3, const_cast<void*>(ptr), dims, strides, box, es, CU_TENSOR_MAP_INTERLEAVE_NONE, sw,
      CU_TENSOR_MAP_L2_PROMOTION_L2_256B, CU_TENSOR_MAP_FLOAT_OOB_FILL_NONE);
}

}

extern "C" void kernel_launch(void* const* d_in, const int* in_sizes, int n_in, void* d_out, int out_size) {
  (void)in_sizes; (void)n_in; (void)out_size;
  PFN_encodeTiled enc = nullptr;
  cudaDriverEntryPointQueryResult qres;
  cudaGetDriverEntryPoint("cuTensorMapEncodeTiled", (void**)&enc, cudaEnableDefault, &qres);
  Params p;
  p.out = (__nv_bfloat16*)d_out;
  cudaGetSymbolAddress((void**)&p.ll, g_ll); cudaGetSymbolAddress((void**)&p.cnt, g_cnt);
  cudaGetSymbolAddress((void**)&p.abT, g_abT); cudaGetSymbolAddress((void**)&p.hT, g_hT);
  p.wd = (const __nv_bfloat16*)d_in[8];
  p.pf[0] = (const char*)d_in[0]; p.pf[1] = (const char*)d_in[3] - 16 * D_ * 2; p.pf[2] = (const char*)d_in[4] - (D_ + 16) * D_ * 2;
  p.pf[3] = (const char*)d_in[6]; p.pf[4] = (const char*)d_in[7];
  Maps maps;
  {
    cuuint64_t dims[5] = {(cuuint64_t)D_, 2, 4, 4, (cuuint64_t)(S_ / 32)};
    cuuint64_t strides[4] = {(cuuint64_t)D_ * 2, (cuuint64_t)D_ * 2 * 8, (cuuint64_t)D_ * 2 * 2, (cuuint64_t)D_ * 2 * 32};
    cuuint32_t box[5] = {64, 2, 4, 4, 4};
    cuuint32_t es[5] = {1, 1, 1, 1, 1};
    enc(&maps.x, CU_TENSOR_MAP_DATA_TYPE_BFLOAT16, 5, d_in[0], dims, strides, box, es, CU_TENSOR_MAP_INTERLEAVE_NONE,
        CU_TENSOR_MAP_SWIZZLE_128B, CU_TENSOR_MAP_L2_PROMOTION_L2_256B, CU_TENSOR_MAP_FLOAT_OOB_FILL_NONE);
    box[4] = 1;
    enc(&maps.o, CU_TENSOR_MAP_DATA_TYPE_BFLOAT16, 5, d_out, dims, strides, box, es, CU_TENSOR_MAP_INTERLEAVE_NONE,
        CU_TENSOR_MAP_SWIZZLE_128B, CU_TENSOR_MAP_L2_PROMOTION_NONE, CU_TENSOR_MAP_FLOAT_OOB_FILL_NONE);
  }
  make_map(enc, &maps.dr, d_in[3], D_, D_, 64, 64, CU_TENSOR_MAP_SWIZZLE_128B);
  make_map(enc, &maps.di, d_in[4], D_, D_, 64, 64, CU_TENSOR_MAP_SWIZZLE_128B);
  make_map(enc, &maps.wg, d_in[6], D_, F_, 64, 64, CU_TENSOR_MAP_SWIZZLE_128B);
  make_map(enc, &maps.wu, d_in[7], D_, F_, 64, 64, CU_TENSOR_MAP_SWIZZLE_128B);
  make_map(enc, &maps.cr, d_in[1], S_, S_, 128, 64, CU_TENSOR_MAP_SWIZZLE_128B);
  make_map(enc, &maps.ci, d_in[2], S_, S_, 128, 64, CU_TENSOR_MAP_SWIZZLE_128B);
  {
    cuuint64_t dims[3] = {256, F_ / 8, S_ / 64};
    cuuint64_t strides[2] = {(cuuint64_t)S_ * 16, 1024};
    cuuint32_t box[3] = {256, 8, 2};
    cuuint32_t es[3] = {1, 1, 1};
    enc(&maps.h, CU_TENSOR_MAP_DATA_TYPE_UINT32, 3, p.hT, dims, strides, box, es, CU_TENSOR_MAP_INTERLEAVE_NONE,
        CU_TENSOR_MAP_SWIZZLE_NONE, CU_TENSOR_MAP_L2_PROMOTION_L2_256B, CU_TENSOR_MAP_FLOAT_OOB_FILL_NONE);
    cuuint64_t dims2[2] = {(cuuint64_t)S_ * 4, 2 * D_ / 8};
    cuuint32_t box2[2] = {256, 10};
    enc(&maps.ab, CU_TENSOR_MAP_DATA_TYPE_UINT32, 2, p.abT, dims2, strides, box2, es, CU_TENSOR_MAP_INTERLEAVE_NONE,
        CU_TENSOR_MAP_SWIZZLE_NONE, CU_TENSOR_MAP_L2_PROMOTION_L2_256B, CU_TENSOR_MAP_FLOAT_OOB_FILL_NONE);
  }
  make_map3(enc, &maps.wd, d_in[8], F_, D_, 32, 32, 5, CU_TENSOR_MAP_SWIZZLE_64B);
  cudaFuncSetAttribute(fused_kernel, cudaFuncAttributeMaxDynamicSharedMemorySize, SMEM_BYTES);
  cudaLaunchConfig_t cfg = {};
  cfg.gridDim = dim3(NUM_CTAS); cfg.blockDim = dim3(384); cfg.dynamicSmemBytes = SMEM_BYTES; cfg.stream = cudaStreamPerThread;
  cudaLaunchAttribute at[1];
  at[0].id = cudaLaunchAttributeClusterDimension; at[0].val.clusterDim.x = 2; at[0].val.clusterDim.y = 1; at[0].val.clusterDim.z = 1;
  cfg.attrs = at; cfg.numAttrs = 1;
  cudaLaunchKernelEx(&cfg, fused_kernel, p, maps);
}
```
